```python
import torch

def _softmax(x, axis=-1):
    return torch.softmax(x, dim=axis)

def _gelu(x):
    return torch.nn.functional.gelu(x, approximate='tanh')

def _silu(x):
    return torch.nn.functional.silu(x)

def _sigmoid(x):
    return torch.sigmoid(x)

def _layernorm(x, axis=-1, eps=1e-05):
    m = x.mean(dim=axis, keepdim=True)
    v = x.var(dim=axis, keepdim=True, unbiased=False)
    return (x - m) / torch.sqrt(v + eps)

def _scatter_add(tgt, idx, src, axis=0):
    return tgt.clone().index_add_(axis, idx, src)

def _segment_sum(src, seg, n):
    out = torch.zeros((n,) + src.shape[1:], dtype=src.dtype)
    return out.index_add_(0, seg, src)

def _pad(x, pw):
    flat = tuple((v for pair in reversed(pw) for v in pair))
    return torch.nn.functional.pad(x, flat)
kernel_name = 'gated_mix__ssm_conv_s5__memory_aug_recurrent_mem_tr__prompt'

def setup_inputs():

    _w = lambda a: (lambda t: t.to(torch.bfloat16) if t.is_floating_point() else t)(torch.as_tensor(a))

    def _A_setup():
        B, S, D = (1, 2048, 448)
        P = D
        Lambda_re = -0.5 * (lambda _x: torch.exp(torch.as_tensor(_x)))((lambda *s: torch.randn(*s, dtype=torch.bfloat16) * 0.8)(P))
        Lambda_im = (lambda *s: torch.randn(*s, dtype=torch.bfloat16) * 0.8)(P) * 1.0
        B_re = (lambda *s: torch.randn(*s, dtype=torch.bfloat16) * 0.8)(P, D) * D ** (-0.5)
        B_im = (lambda *s: torch.randn(*s, dtype=torch.bfloat16) * 0.8)(P, D) * D ** (-0.5)
        C_re = (lambda *s: torch.randn(*s, dtype=torch.bfloat16) * 0.8)(D, P) * P ** (-0.5)
        C_im = (lambda *s: torch.randn(*s, dtype=torch.bfloat16) * 0.8)(D, P) * P ** (-0.5)
        log_dt = (lambda *s: torch.randn(*s, dtype=torch.bfloat16) * 0.8)(P) * 0.3 - 2.0
        Dskip = (lambda *s: torch.randn(*s, dtype=torch.bfloat16) * 0.8)(D)
        return {'x': _w((lambda *s: torch.randn(*s, dtype=torch.bfloat16) * 0.05)(B, S, D)), 'Lambda_re': _w(Lambda_re), 'Lambda_im': _w(Lambda_im), 'B_re': _w(B_re), 'B_im': _w(B_im), 'C_re': _w(C_re), 'C_im': _w(C_im), 'log_dt': _w(log_dt), 'Dskip': _w(Dskip)}
    _A_in = _A_setup()

    def _B_setup():
        B, S, Dm = (1, 2048, 448)
        H, Dh = (16, 256)
        M, seg = (8, 32)
        seg = min(seg, S)
        S = S // seg * seg
        return {'x': _w((lambda *s: torch.randn(*s, dtype=torch.bfloat16) * 0.05)(B, S, Dm)), 'mem0': _w((lambda *s: torch.randn(*s, dtype=torch.bfloat16) * 0.8)(B, M, Dm)), 'Wq': _w((lambda *s: torch.randn(*s, dtype=torch.bfloat16) * 3.2)(Dm, H, Dh) * Dm ** (-0.5)), 'Wk': _w((lambda *s: torch.randn(*s, dtype=torch.bfloat16) * 3.2)(Dm, H, Dh) * Dm ** (-0.5)), 'Wv': _w((lambda *s: torch.randn(*s, dtype=torch.bfloat16) * 0.8)(Dm, H, Dh) * Dm ** (-0.5)), 'Wo': _w((lambda *s: torch.randn(*s, dtype=torch.bfloat16) * 0.8)(H, Dh, Dm) * (H * Dh) ** (-0.5)), 'seg_len': seg}
    _B_in = _B_setup()
    return {'A_x': _A_in['x'], 'A_Lambda_re': _A_in['Lambda_re'], 'A_Lambda_im': _A_in['Lambda_im'], 'A_B_re': _A_in['B_re'], 'A_B_im': _A_in['B_im'], 'A_C_re': _A_in['C_re'], 'A_C_im': _A_in['C_im'], 'A_log_dt': _A_in['log_dt'], 'A_Dskip': _A_in['Dskip'], 'B_x': _B_in['x'], 'B_mem0': _B_in['mem0'], 'B_Wq': _B_in['Wq'], 'B_Wk': _B_in['Wk'], 'B_Wv': _B_in['Wv'], 'B_Wo': _B_in['Wo'], 'B_seg_len': _B_in['seg_len'], 'gate_w': _w((lambda *s: torch.randn(*s, dtype=torch.bfloat16) * 0.05)(448) * 16.0)}

def reference(A_x, A_Lambda_re, A_Lambda_im, A_B_re, A_B_im, A_C_re, A_C_im, A_log_dt, A_Dskip, B_x, B_mem0, B_Wq, B_Wk, B_Wv, B_Wo, B_seg_len, gate_w):

    def _A_ref(x, Lambda_re, Lambda_im, B_re, B_im, C_re, C_im, log_dt, Dskip):
        Bsz, L, H = x.shape
        Lam = Lambda_re + 1j * Lambda_im
        Bmat = B_re + 1j * B_im
        Cmat = C_re + 1j * C_im
        dt = torch.exp(log_dt)
        Lam_bar = torch.exp(dt * Lam)
        B_bar = ((Lam_bar - 1.0) / Lam)[:, None] * Bmat
        Bu = torch.einsum('bld,pd->blp', x + 0j, B_bar)
        h = torch.zeros_like(Bu[:, 0, :])
        hs = []
        for t in range(L):
            h = Lam_bar[None, :] * h + Bu[:, t, :]
            hs.append(h)
        hseq = torch.stack(hs, 1)
        y = 2.0 * torch.einsum('blp,dp->bld', hseq, Cmat).real + x * Dskip[None, None, :]
        return y

    def _B_ref(x, mem0, Wq, Wk, Wv, Wo, seg_len):
        B, S, Dm = x.shape
        H, Dh = (Wq.shape[1], Wq.shape[2])
        M = mem0.shape[1]
        scale = Dh ** (-0.5)
        n_seg = S // seg_len
        L = M + seg_len
        idx = torch.arange(L)
        mask = (idx[:, None] < M) | (idx[:, None] >= idx[None, :])
        mem = mem0
        outs = []
        for s in range(n_seg):
            xs = x[:, s * seg_len:(s + 1) * seg_len, :].clone()
            h = torch.concatenate([mem, xs], axis=1)
            q = torch.einsum('btd,dhe->bhte', h, Wq)
            k = torch.einsum('btd,dhe->bhte', h, Wk)
            v = torch.einsum('btd,dhe->bhte', h, Wv)
            scores = torch.einsum('bhqe,bhke->bhqk', q, k) * scale
            scores = torch.where(mask[None, None], scores, -1000000000.0)
            p = _softmax(scores, axis=-1)
            o = torch.einsum('bhqk,bhke->bhqe', p, v)
            o = torch.einsum('bhte,hed->btd', o, Wo)
            mem = o[:, :M, :].clone()
            outs.append(o[:, M:, :])
        return torch.concatenate(outs, axis=1)
    x = A_x
    g = _sigmoid((x * gate_w).sum(-1, keepdims=True))
    a = _A_ref(x, A_Lambda_re, A_Lambda_im, A_B_re, A_B_im, A_C_re, A_C_im, A_log_dt, A_Dskip)
    b = _B_ref(x, B_mem0, B_Wq, B_Wk, B_Wv, B_Wo, B_seg_len)
    return g * a + (1 - g) * b
```

```cpp
#include <cuda_runtime.h>
#include <cuda_bf16.h>
#include <cuda.h>
#include <stdint.h>

typedef __nv_bfloat16 bf16;

namespace {

constexpr int NH = 16, DM = 448, DH = 256, SEQ = 2048, SEG = 32, NSEG = 64, NJ = 7, NMEM = 8, LKEY = 40;
constexpr int SPIN_LIMIT = 1 << 22;

__device__ __forceinline__ uint32_t smem_u32(const void* p) { return (uint32_t)__cvta_generic_to_shared(p); }
__device__ __forceinline__ void mbar_init(uint32_t a, uint32_t c) { asm volatile("mbarrier.init.shared.b64 [%0], %1;" ::"r"(a), "r"(c)); }
__device__ __forceinline__ void mbar_arrive(uint32_t a) { asm volatile("mbarrier.arrive.shared.b64 _, [%0];" ::"r"(a) : "memory"); }
__device__ __forceinline__ void mbar_expect_tx(uint32_t a, uint32_t b) { asm volatile("mbarrier.arrive.expect_tx.shared.b64 _, [%0], %1;" ::"r"(a), "r"(b) : "memory"); }
__device__ __forceinline__ bool mbar_try(uint32_t a, uint32_t parity) {
  uint32_t r;
  asm volatile("{\n.reg .pred p;\nmbarrier.try_wait.parity.shared.b64 p, [%1], %2;\nselp.u32 %0, 1, 0, p;\n}\n" : "=r"(r) : "r"(a), "r"(parity) : "memory");
  return r;
}
__device__ __forceinline__ bool mbar_try_cluster(uint32_t a, uint32_t parity) {
  uint32_t r;
  asm volatile("{\n.reg .pred p;\nmbarrier.try_wait.parity.acquire.cluster.shared.b64 p, [%1], %2;\nselp.u32 %0, 1, 0, p;\n}\n" : "=r"(r) : "r"(a), "r"(parity) : "memory");
  return r;
}
__device__ __forceinline__ bool mbar_test(uint32_t a, uint32_t parity) {
  uint32_t r;
  asm volatile("{\n.reg .pred p;\nmbarrier.test_wait.parity.shared.b64 p, [%1], %2;\nselp.u32 %0, 1, 0, p;\n}\n" : "=r"(r) : "r"(a), "r"(parity) : "memory");
  return r;
}
__device__ __forceinline__ void mbar_wait(uint32_t a, uint32_t parity) {
  int it = 0;
  while (!mbar_try(a, parity)) { if (++it > SPIN_LIMIT) break; }
}
__device__ __forceinline__ void mbar_wait_cluster(uint32_t a, uint32_t parity) {
  int it = 0;
  while (!mbar_try_cluster(a, parity)) { if (++it > SPIN_LIMIT) break; }
}
__device__ __forceinline__ uint32_t mapa(uint32_t a, uint32_t r) { uint32_t d; asm volatile("mapa.shared::cluster.u32 %0, %1, %2;" : "=r"(d) : "r"(a), "r"(r)); return d; }
__device__ __forceinline__ void cluster_sync_all() { asm volatile("barrier.cluster.arrive.aligned;\nbarrier.cluster.wait.aligned;" ::: "memory"); }
__device__ __forceinline__ void named_bar(int id, int n) { asm volatile("bar.sync %0, %1;" ::"r"(id), "r"(n) : "memory"); }
__device__ __forceinline__ void fence_async_smem() { asm volatile("fence.proxy.async.shared::cta;" ::: "memory"); }
__device__ __forceinline__ void fence_async_all() { asm volatile("fence.proxy.async;" ::: "memory"); }

__device__ __forceinline__ uint4 ld_vol_v4(const void* p) {
  uint4 v;
  asm volatile("ld.volatile.global.v4.u32 {%0,%1,%2,%3}, [%4];" : "=r"(v.x), "=r"(v.y), "=r"(v.z), "=r"(v.w) : "l"(p) : "memory");
  return v;
}
__device__ __forceinline__ uint32_t ld_acquire(const void* p) { uint32_t v; asm volatile("ld.acquire.gpu.global.u32 %0, [%1];" : "=r"(v) : "l"(p) : "memory"); return v; }
__device__ __forceinline__ void st_relaxed(void* p, uint32_t v) { asm volatile("st.relaxed.gpu.global.u32 [%0], %1;" ::"l"(p), "r"(v) : "memory"); }
__device__ __forceinline__ void red_v4(void* p, float a, float b, float c, float d) {
  asm volatile("red.relaxed.gpu.global.add.v4.f32 [%0], {%1,%2,%3,%4};" ::"l"(p), "f"(a), "f"(b), "f"(c), "f"(d) : "memory");
}
__device__ __forceinline__ void red_v2(void* p, float a, float b) {
  asm volatile("red.relaxed.gpu.global.add.v2.f32 [%0], {%1,%2};" ::"l"(p), "f"(a), "f"(b) : "memory");
}
__device__ __forceinline__ void red_u32(void* p, uint32_t v) { asm volatile("red.relaxed.gpu.global.add.u32 [%0], %1;" ::"l"(p), "r"(v) : "memory"); }
__device__ __forceinline__ void st_async_v4(uint32_t addr, float a, float b, float c, float d, uint32_t mbar) {
  asm volatile("st.async.shared::cluster.mbarrier::complete_tx::bytes.v4.f32 [%0], {%1,%2,%3,%4}, [%5];" ::"r"(addr), "f"(a), "f"(b), "f"(c), "f"(d), "r"(mbar) : "memory");
}

__device__ __forceinline__ void tma_load_2d(uint32_t dst, const CUtensorMap* tm, int c0, int c1, uint32_t mbar) {
  asm volatile("cp.async.bulk.tensor.2d.shared::cluster.global.mbarrier::complete_tx::bytes [%0], [%1, {%3, %4}], [%2];" ::"r"(dst), "l"(tm), "r"(mbar), "r"(c0), "r"(c1) : "memory");
}
__device__ __forceinline__ void tma_load_2d_mc(uint32_t dst, const CUtensorMap* tm, int c0, int c1, uint32_t mbar, uint16_t mask) {
  asm volatile("cp.async.bulk.tensor.2d.shared::cluster.global.mbarrier::complete_tx::bytes.multicast::cluster [%0], [%1, {%3, %4}], [%2], %5;" ::"r"(dst), "l"(tm), "r"(mbar), "r"(c0), "r"(c1), "h"(mask) : "memory");
}
__device__ __forceinline__ void tma_load_4d(uint32_t dst, const CUtensorMap* tm, int c0, int c1, int c2, int c3, uint32_t mbar) {
  asm volatile("cp.async.bulk.tensor.4d.shared::cluster.global.mbarrier::complete_tx::bytes [%0], [%1, {%3, %4, %5, %6}], [%2];" ::"r"(dst), "l"(tm), "r"(mbar), "r"(c0), "r"(c1), "r"(c2), "r"(c3) : "memory");
}
__device__ __forceinline__ void tma_store_2d(const CUtensorMap* tm, int c0, int c1, uint32_t src) {
  asm volatile("cp.async.bulk.tensor.2d.global.shared::cta.bulk_group [%0, {%2, %3}], [%1];" ::"l"(tm), "r"(src), "r"(c0), "r"(c1) : "memory");
}
__device__ __forceinline__ void bulk_load(uint32_t dst, const void* src, uint32_t bytes, uint32_t mbar) {
  asm volatile("cp.async.bulk.shared::cluster.global.mbarrier::complete_tx::bytes [%0], [%1], %2, [%3];" ::"r"(dst), "l"(src), "r"(bytes), "r"(mbar) : "memory");
}
__device__ __forceinline__ void bulk_commit() { asm volatile("cp.async.bulk.commit_group;" ::: "memory"); }
template <int N> __device__ __forceinline__ void bulk_wait_read() { asm volatile("cp.async.bulk.wait_group.read %0;" ::"n"(N) : "memory"); }
template <int N> __device__ __forceinline__ void bulk_wait() { asm volatile("cp.async.bulk.wait_group %0;" ::"n"(N) : "memory"); }

__device__ __forceinline__ void wg_fence() { asm volatile("wgmma.fence.sync.aligned;" ::: "memory"); }
__device__ __forceinline__ void wg_commit() { asm volatile("wgmma.commit_group.sync.aligned;" ::: "memory"); }
template <int N> __device__ __forceinline__ void wg_wait() { asm volatile("wgmma.wait_group.sync.aligned %0;" ::"n"(N) : "memory"); }

__device__ __forceinline__ uint64_t desc_sw128(uint32_t addr) {
  return ((uint64_t)((addr & 0x3FFFF) >> 4)) | ((uint64_t)1 << 16) | ((uint64_t)(1024 >> 4) << 32) | ((uint64_t)1 << 62);
}

__device__ __forceinline__ uint32_t pack_bf16(float lo, float hi) {
  uint32_t r;
  asm("cvt.rn.bf16x2.f32 %0, %1, %2;" : "=r"(r) : "f"(hi), "f"(lo));
  return r;
}
__device__ __forceinline__ void mma16816(float* d, uint32_t a0, uint32_t a1, uint32_t a2, uint32_t a3, uint32_t b0, uint32_t b1) {
  asm volatile("mma.sync.aligned.m16n8k16.row.col.f32.bf16.bf16.f32 {%0,%1,%2,%3}, {%4,%5,%6,%7}, {%8,%9}, {%0,%1,%2,%3};"
               : "+f"(d[0]), "+f"(d[1]), "+f"(d[2]), "+f"(d[3]) : "r"(a0), "r"(a1), "r"(a2), "r"(a3), "r"(b0), "r"(b1));
}
__device__ __forceinline__ void mma1688(float* d, uint32_t a0, uint32_t a1, uint32_t b0) {
  asm volatile("mma.sync.aligned.m16n8k8.row.col.f32.bf16.bf16.f32 {%0,%1,%2,%3}, {%4,%5}, {%6}, {%0,%1,%2,%3};"
               : "+f"(d[0]), "+f"(d[1]), "+f"(d[2]), "+f"(d[3]) : "r"(a0), "r"(a1), "r"(b0));
}
__device__ __forceinline__ void ldsm_x4(uint32_t* r, uint32_t addr) {
  asm volatile("ldmatrix.sync.aligned.m8n8.x4.shared.b16 {%0,%1,%2,%3}, [%4];" : "=r"(r[0]), "=r"(r[1]), "=r"(r[2]), "=r"(r[3]) : "r"(addr) : "memory");
}
__device__ __forceinline__ void ldsm_x4_t(uint32_t* r, uint32_t addr) {
  asm volatile("ldmatrix.sync.aligned.m8n8.x4.trans.shared.b16 {%0,%1,%2,%3}, [%4];" : "=r"(r[0]), "=r"(r[1]), "=r"(r[2]), "=r"(r[3]) : "r"(addr) : "memory");
}
__device__ __forceinline__ void ldsm_x2_t(uint32_t* r, uint32_t addr) {
  asm volatile("ldmatrix.sync.aligned.m8n8.x2.trans.shared.b16 {%0,%1}, [%2];" : "=r"(r[0]), "=r"(r[1]) : "r"(addr) : "memory");
}
__device__ __forceinline__ void stsm_x4_t(uint32_t addr, uint32_t r0, uint32_t r1, uint32_t r2, uint32_t r3) {
  asm volatile("stmatrix.sync.aligned.m8n8.x4.trans.shared.b16 [%0], {%1,%2,%3,%4};" ::"r"(addr), "r"(r0), "r"(r1), "r"(r2), "r"(r3) : "memory");
}
__device__ __forceinline__ uint32_t movm_t(uint32_t a) { uint32_t d; asm volatile("movmatrix.sync.aligned.m8n8.trans.b16 %0, %1;" : "=r"(d) : "r"(a)); return d; }
__device__ __forceinline__ float ex2(float x) { float y; asm("ex2.approx.ftz.f32 %0, %1;" : "=f"(y) : "f"(x)); return y; }

__device__ __forceinline__ void wgmma_ss_n112(float* d, uint64_t descA, uint64_t descB, int scaleD) {
  asm volatile("{\n.reg .pred p;\nsetp.ne.b32 p, %58, 0;\n"
    "wgmma.mma_async.sync.aligned.m64n112k16.f32.bf16.bf16 {%0,%1,%2,%3,%4,%5,%6,%7,%8,%9,%10,%11,%12,%13,%14,%15,%16,%17,%18,%19,%20,%21,%22,%23,%24,%25,%26,%27,%28,%29,%30,%31,%32,%33,%34,%35,%36,%37,%38,%39,%40,%41,%42,%43,%44,%45,%46,%47,%48,%49,%50,%51,%52,%53,%54,%55}, %56, %57, p, 1, 1, 0, 0;\n}\n"
    : "+f"(d[0]),"+f"(d[1]),"+f"(d[2]),"+f"(d[3]),"+f"(d[4]),"+f"(d[5]),"+f"(d[6]),"+f"(d[7]),"+f"(d[8]),"+f"(d[9]),"+f"(d[10]),"+f"(d[11]),"+f"(d[12]),"+f"(d[13]),"+f"(d[14]),"+f"(d[15]),"+f"(d[16]),"+f"(d[17]),"+f"(d[18]),"+f"(d[19]),"+f"(d[20]),"+f"(d[21]),"+f"(d[22]),"+f"(d[23]),"+f"(d[24]),"+f"(d[25]),"+f"(d[26]),"+f"(d[27]),"+f"(d[28]),"+f"(d[29]),"+f"(d[30]),"+f"(d[31]),"+f"(d[32]),"+f"(d[33]),"+f"(d[34]),"+f"(d[35]),"+f"(d[36]),"+f"(d[37]),"+f"(d[38]),"+f"(d[39]),"+f"(d[40]),"+f"(d[41]),"+f"(d[42]),"+f"(d[43]),"+f"(d[44]),"+f"(d[45]),"+f"(d[46]),"+f"(d[47]),"+f"(d[48]),"+f"(d[49]),"+f"(d[50]),"+f"(d[51]),"+f"(d[52]),"+f"(d[53]),"+f"(d[54]),"+f"(d[55])
    : "l"(descA), "l"(descB), "r"(scaleD));
}
__device__ __forceinline__ void wgmma_ss_n112_ta(float* d, uint64_t descA, uint64_t descB, int scaleD) {
  asm volatile("{\n.reg .pred p;\nsetp.ne.b32 p, %58, 0;\n"
    "wgmma.mma_async.sync.aligned.m64n112k16.f32.bf16.bf16 {%0,%1,%2,%3,%4,%5,%6,%7,%8,%9,%10,%11,%12,%13,%14,%15,%16,%17,%18,%19,%20,%21,%22,%23,%24,%25,%26,%27,%28,%29,%30,%31,%32,%33,%34,%35,%36,%37,%38,%39,%40,%41,%42,%43,%44,%45,%46,%47,%48,%49,%50,%51,%52,%53,%54,%55}, %56, %57, p, 1, 1, 1, 0;\n}\n"
    : "+f"(d[0]),"+f"(d[1]),"+f"(d[2]),"+f"(d[3]),"+f"(d[4]),"+f"(d[5]),"+f"(d[6]),"+f"(d[7]),"+f"(d[8]),"+f"(d[9]),"+f"(d[10]),"+f"(d[11]),"+f"(d[12]),"+f"(d[13]),"+f"(d[14]),"+f"(d[15]),"+f"(d[16]),"+f"(d[17]),"+f"(d[18]),"+f"(d[19]),"+f"(d[20]),"+f"(d[21]),"+f"(d[22]),"+f"(d[23]),"+f"(d[24]),"+f"(d[25]),"+f"(d[26]),"+f"(d[27]),"+f"(d[28]),"+f"(d[29]),"+f"(d[30]),"+f"(d[31]),"+f"(d[32]),"+f"(d[33]),"+f"(d[34]),"+f"(d[35]),"+f"(d[36]),"+f"(d[37]),"+f"(d[38]),"+f"(d[39]),"+f"(d[40]),"+f"(d[41]),"+f"(d[42]),"+f"(d[43]),"+f"(d[44]),"+f"(d[45]),"+f"(d[46]),"+f"(d[47]),"+f"(d[48]),"+f"(d[49]),"+f"(d[50]),"+f"(d[51]),"+f"(d[52]),"+f"(d[53]),"+f"(d[54]),"+f"(d[55])
    : "l"(descA), "l"(descB), "r"(scaleD));
}
__device__ __forceinline__ void wgmma_rs_n32(float* d, const uint32_t* a, uint64_t descB, int scaleD) {
  asm volatile("{\n.reg .pred p;\nsetp.ne.b32 p, %21, 0;\n"
    "wgmma.mma_async.sync.aligned.m64n32k16.f32.bf16.bf16 {%0,%1,%2,%3,%4,%5,%6,%7,%8,%9,%10,%11,%12,%13,%14,%15}, {%16,%17,%18,%19}, %20, p, 1, 1, 0;\n}\n"
    : "+f"(d[0]),"+f"(d[1]),"+f"(d[2]),"+f"(d[3]),"+f"(d[4]),"+f"(d[5]),"+f"(d[6]),"+f"(d[7]),"+f"(d[8]),"+f"(d[9]),"+f"(d[10]),"+f"(d[11]),"+f"(d[12]),"+f"(d[13]),"+f"(d[14]),"+f"(d[15])
    : "r"(a[0]), "r"(a[1]), "r"(a[2]), "r"(a[3]), "l"(descB), "r"(scaleD));
}
__device__ __forceinline__ void wgmma_ss_n128(float* d, uint64_t descA, uint64_t descB, int scaleD) {
  asm volatile("{\n.reg .pred p;\nsetp.ne.b32 p, %66, 0;\n"
    "wgmma.mma_async.sync.aligned.m64n128k16.f32.bf16.bf16 {%0,%1,%2,%3,%4,%5,%6,%7,%8,%9,%10,%11,%12,%13,%14,%15,%16,%17,%18,%19,%20,%21,%22,%23,%24,%25,%26,%27,%28,%29,%30,%31,%32,%33,%34,%35,%36,%37,%38,%39,%40,%41,%42,%43,%44,%45,%46,%47,%48,%49,%50,%51,%52,%53,%54,%55,%56,%57,%58,%59,%60,%61,%62,%63}, %64, %65, p, 1, 1, 0, 0;\n}\n"
    : "+f"(d[0]),"+f"(d[1]),"+f"(d[2]),"+f"(d[3]),"+f"(d[4]),"+f"(d[5]),"+f"(d[6]),"+f"(d[7]),"+f"(d[8]),"+f"(d[9]),"+f"(d[10]),"+f"(d[11]),"+f"(d[12]),"+f"(d[13]),"+f"(d[14]),"+f"(d[15]),"+f"(d[16]),"+f"(d[17]),"+f"(d[18]),"+f"(d[19]),"+f"(d[20]),"+f"(d[21]),"+f"(d[22]),"+f"(d[23]),"+f"(d[24]),"+f"(d[25]),"+f"(d[26]),"+f"(d[27]),"+f"(d[28]),"+f"(d[29]),"+f"(d[30]),"+f"(d[31]),"+f"(d[32]),"+f"(d[33]),"+f"(d[34]),"+f"(d[35]),"+f"(d[36]),"+f"(d[37]),"+f"(d[38]),"+f"(d[39]),"+f"(d[40]),"+f"(d[41]),"+f"(d[42]),"+f"(d[43]),"+f"(d[44]),"+f"(d[45]),"+f"(d[46]),"+f"(d[47]),"+f"(d[48]),"+f"(d[49]),"+f"(d[50]),"+f"(d[51]),"+f"(d[52]),"+f"(d[53]),"+f"(d[54]),"+f"(d[55]),"+f"(d[56]),"+f"(d[57]),"+f"(d[58]),"+f"(d[59]),"+f"(d[60]),"+f"(d[61]),"+f"(d[62]),"+f"(d[63])
    : "l"(descA), "l"(descB), "r"(scaleD));
}
__device__ __forceinline__ void wgmma_ss_n40(float* d, uint64_t descA, uint64_t descB, int scaleD) {
  asm volatile("{\n.reg .pred p;\nsetp.ne.b32 p, %22, 0;\n"
    "wgmma.mma_async.sync.aligned.m64n40k16.f32.bf16.bf16 {%0,%1,%2,%3,%4,%5,%6,%7,%8,%9,%10,%11,%12,%13,%14,%15,%16,%17,%18,%19}, %20, %21, p, 1, 1, 0, 0;\n}\n"
    : "+f"(d[0]),"+f"(d[1]),"+f"(d[2]),"+f"(d[3]),"+f"(d[4]),"+f"(d[5]),"+f"(d[6]),"+f"(d[7]),"+f"(d[8]),"+f"(d[9]),"+f"(d[10]),"+f"(d[11]),"+f"(d[12]),"+f"(d[13]),"+f"(d[14]),"+f"(d[15]),"+f"(d[16]),"+f"(d[17]),"+f"(d[18]),"+f"(d[19])
    : "l"(descA), "l"(descB), "r"(scaleD));
}
__device__ __forceinline__ void wgmma_rs_n64_tb(float* d, const uint32_t* a, uint64_t descB, int scaleD) {
  asm volatile("{\n.reg .pred p;\nsetp.ne.b32 p, %37, 0;\n"
    "wgmma.mma_async.sync.aligned.m64n64k16.f32.bf16.bf16 {%0,%1,%2,%3,%4,%5,%6,%7,%8,%9,%10,%11,%12,%13,%14,%15,%16,%17,%18,%19,%20,%21,%22,%23,%24,%25,%26,%27,%28,%29,%30,%31}, {%32,%33,%34,%35}, %36, p, 1, 1, 1;\n}\n"
    : "+f"(d[0]),"+f"(d[1]),"+f"(d[2]),"+f"(d[3]),"+f"(d[4]),"+f"(d[5]),"+f"(d[6]),"+f"(d[7]),"+f"(d[8]),"+f"(d[9]),"+f"(d[10]),"+f"(d[11]),"+f"(d[12]),"+f"(d[13]),"+f"(d[14]),"+f"(d[15]),"+f"(d[16]),"+f"(d[17]),"+f"(d[18]),"+f"(d[19]),"+f"(d[20]),"+f"(d[21]),"+f"(d[22]),"+f"(d[23]),"+f"(d[24]),"+f"(d[25]),"+f"(d[26]),"+f"(d[27]),"+f"(d[28]),"+f"(d[29]),"+f"(d[30]),"+f"(d[31])
    : "r"(a[0]), "r"(a[1]), "r"(a[2]), "r"(a[3]), "l"(descB), "r"(scaleD));
}
struct ChainArgs {
  const bf16* mem0;
  uint32_t* Mg;
  float4* Sg;
  uint32_t* flag;
  uint32_t* dbg;
};

constexpr int XT_BYTES = 28672;
constexpr int STG_BYTES = 5120;
constexpr int OFF_A = 0, OFF_B = 65536, OFF_C = OFF_B + 3 * XT_BYTES, OFF_M = OFF_C + 2 * XT_BYTES, OFF_P = OFF_M + 2 * 7168,
              OFF_SX = OFF_P + 4096, OFF_SM = OFF_SX + 2048, OFF_SW = OFF_SM + 512, OFF_BAR = OFF_SW + 1024, OFF_DBG = OFF_B + 2 * XT_BYTES + 3 * 7168, SMEM_CHAIN = OFF_BAR + 512;
enum { B_PA = 0, B_PE = 1, B_XF = 4, B_MB = 9, B_SX = 11, B_SM = 13, B_PB = 15, B_KR = 17, B_ST = 21, B_PF = 29, B_RD = 45, B_MF = 47, B_EM = 51, B_SB = 55, B_NUM = 56 };
#define MD0 250
#define MDELTA 900
#define SSTART 850
#define SXSTART 700
#define SSTAG 130
constexpr float L2E = 1.4426950408889634f;
constexpr int CHAIN_THREADS = 512;
#define TOKK 28

__device__ __forceinline__ uint32_t xstage_off(int st) { return st < 2 ? OFF_C + st * XT_BYTES : OFF_B + (st - 2) * XT_BYTES; }
__device__ __forceinline__ uint32_t mslot_off(int k) { return k < 3 ? OFF_B + 2 * XT_BYTES + k * 7168 : OFF_M; }
constexpr int OFF_VAR = OFF_BAR + 480;

__device__ __forceinline__ bool slot_has_sentinel(const uint8_t* p, int lane) {
  bool bad = false;
#pragma unroll 2
  for (int i = 0; i < 14; i++) { const uint4 v = *reinterpret_cast<const uint4*>(p + (32 * i + lane) * 16); bad |= (v.x == ~0u) | (v.y == ~0u) | (v.z == ~0u) | (v.w == ~0u); }
  return __any_sync(~0u, bad);
}
__device__ __forceinline__ uint32_t clk32() { uint32_t c; asm volatile("mov.u32 %0, %%clock;" : "=r"(c)); return c; }
#define DBG(slot) do {} while (0)

template <bool CL>
__device__ __forceinline__ void issue_x_load(uint32_t sb, const CUtensorMap* tm_x, int seg, int rank) {
  const int st = seg & 3;
  const uint32_t bar = sb + OFF_BAR + (B_XF + st) * 8;
  const uint32_t dst = sb + xstage_off(st);
  mbar_expect_tx(bar, XT_BYTES);
  if (CL) {
    if (rank < NJ) tma_load_2d_mc(dst + rank * 4096, tm_x, rank * 64, seg * SEG, bar, (uint16_t)0xFFFF);
  } else {
#pragma unroll
    for (int c = 0; c < NJ; c++) tma_load_2d(dst + c * 4096, tm_x, c * 64, seg * SEG, bar);
  }
}

template <int WG>
__device__ __forceinline__ void tile_prologue(uint32_t* W, uint32_t sb) {
  const uint32_t bar = sb + OFF_BAR;
  const int lane = threadIdx.x & 31;
  float acc[112];
  mbar_wait(bar + B_PA * 8, 0);
#pragma unroll
  for (int half = 0; half < 2; half++) {
#pragma unroll
    for (int ec = 0; ec < 4; ec++) {
      const int i = half * 8 + ec * 2 + WG;
      const int st = i % 3;
      mbar_wait(bar + (B_PF + i) * 8, 0);
      const uint32_t bb = sb + OFF_B + st * XT_BYTES;
      wg_fence();
#pragma unroll
      for (int kk = 0; kk < 4; kk++) {
        if (WG == 0) {
          wgmma_ss_n112(acc, desc_sw128(sb + OFF_A + ec * 8192 + kk * 32), desc_sw128(bb + kk * 32), (ec | kk) != 0);
          wgmma_ss_n112(acc + 56, desc_sw128(sb + OFF_A + ec * 8192 + kk * 32), desc_sw128(bb + 14336 + kk * 32), (ec | kk) != 0);
        } else {
          wgmma_ss_n112_ta(acc, desc_sw128(sb + OFF_A + 32768 + (ec * 64 + kk * 16) * 128), desc_sw128(bb + kk * 32), (ec | kk) != 0);
          wgmma_ss_n112_ta(acc + 56, desc_sw128(sb + OFF_A + 32768 + (ec * 64 + kk * 16) * 128), desc_sw128(bb + 14336 + kk * 32), (ec | kk) != 0);
        }
      }
      wg_commit();
      wg_wait<0>();
      if (lane == 0) mbar_arrive(bar + (B_PE + st) * 8);
    }
    const float sc = WG == 0 ? 0.0625f : 1.0f;
#pragma unroll
    for (int kk = 0; kk < 14; kk++) {
      W[half * 56 + kk * 4 + 0] = pack_bf16(acc[8 * kk + 0] * sc, acc[8 * kk + 1] * sc);
      W[half * 56 + kk * 4 + 1] = pack_bf16(acc[8 * kk + 2] * sc, acc[8 * kk + 3] * sc);
      W[half * 56 + kk * 4 + 2] = pack_bf16(acc[8 * kk + 4] * sc, acc[8 * kk + 5] * sc);
      W[half * 56 + kk * 4 + 3] = pack_bf16(acc[8 * kk + 6] * sc, acc[8 * kk + 7] * sc);
    }
  }
}

__device__ __forceinline__ void token_gemm(const uint32_t* W, uint32_t sb, int seg, uint32_t stg_base, int w, int lane) {
  const int st = seg & 3;
  mbar_wait(sb + OFF_BAR + (B_XF + st) * 8, (seg >> 2) & 1);
  const uint32_t xb = sb + xstage_off(st);
  float d[16];
  wg_fence();
#pragma unroll
  for (int kk = 0; kk < TOKK; kk++) wgmma_rs_n32(d, &W[4 * kk], desc_sw128(xb + (kk >> 2) * 4096 + (kk & 3) * 32), kk != 0);
  wg_commit();
  wg_wait<0>();
  const uint32_t stg = stg_base + (seg & 3) * STG_BYTES + 1024;
  const int r = lane & 7, mi = lane >> 3;
#pragma unroll
  for (int p = 0; p < 2; p++) {
    const int t = 8 * (2 * p + (mi >> 1)) + r;
    const int chunk = 2 * w + (mi & 1);
    const uint32_t addr = stg + t * 128 + ((chunk ^ r) << 4);
    stsm_x4_t(addr, pack_bf16(d[8 * p + 0], d[8 * p + 1]), pack_bf16(d[8 * p + 2], d[8 * p + 3]), pack_bf16(d[8 * p + 4], d[8 * p + 5]),
              pack_bf16(d[8 * p + 6], d[8 * p + 7]));
  }
}

__device__ __forceinline__ void poll_smm(uint8_t* smem, uint32_t bar, const float4* src, int s, int p, int lane) {
  volatile uint32_t* var = reinterpret_cast<volatile uint32_t*>(smem + OFF_VAR);
  { int it = 0; while (var[1] != (uint32_t)s && ++it < SPIN_LIMIT) __nanosleep(20); }
  const uint32_t tM = clk32();
  while ((int)(clk32() - tM) < SSTART + p * SSTAG) {}
  uint4 v; int it = 0; bool mine = true;
  while (true) {
    v = ld_vol_v4(src);
    if (__all_sync(~0u, __uint_as_float(v.z) == 7.f)) break;
    if (mbar_test(bar + (B_SM + (s & 1)) * 8, (s >> 1) & 1)) { mine = false; break; }
    if (++it > SPIN_LIMIT) break;
  }
  if (mine) {
    reinterpret_cast<float2*>(smem + OFF_SM + (s & 1) * 256)[lane] = make_float2(__uint_as_float(v.x), __uint_as_float(v.y));
    __syncwarp();
    if (lane == 0) { if (atomicExch(reinterpret_cast<uint32_t*>(smem + OFF_VAR), (uint32_t)(s + 1)) != (uint32_t)(s + 1)) mbar_arrive(bar + (B_SM + (s & 1)) * 8); }
  }
}

template <bool CL>
__global__ void __launch_bounds__(CHAIN_THREADS, 1)
chain_kernel(const __grid_constant__ CUtensorMap tm_x, const __grid_constant__ CUtensorMap tm_wq, const __grid_constant__ CUtensorMap tm_wk,
             const __grid_constant__ CUtensorMap tm_wv, const __grid_constant__ CUtensorMap tm_wo, const __grid_constant__ CUtensorMap tm_k,
             const __grid_constant__ CUtensorMap tm_y, ChainArgs args) {
  extern __shared__ __align__(1024) uint8_t smem[];
  const uint32_t sb = smem_u32(smem);
  const int tid = threadIdx.x, warp = tid >> 5, lane = tid & 31;
  const int j = blockIdx.x >> 4, h = blockIdx.x & 15;
  const uint32_t bar = sb + OFF_BAR;
  const int g = lane >> 2, q = lane & 3;

  if (tid == 0) {
    mbar_init(bar + B_PA * 8, 1);
    for (int i = 0; i < 3; i++) mbar_init(bar + (B_PE + i) * 8, 4);
    for (int i = 0; i < 16; i++) mbar_init(bar + (B_PF + i) * 8, 1);
    for (int i = 0; i < 5; i++) mbar_init(bar + (B_XF + i) * 8, 1);
    for (int i = 0; i < 2; i++) {
      mbar_init(bar + (B_SX + i) * 8, 4); mbar_init(bar + (B_SM + i) * 8, 1); mbar_init(bar + (B_PB + i) * 8, 1); mbar_init(bar + (B_RD + i) * 8, 1);
    }
    for (int i = 0; i < 4; i++) { mbar_init(bar + (B_KR + i) * 8, 4); mbar_init(bar + (B_MF + i) * 8, 1); mbar_init(bar + (B_EM + i) * 8, 4); }
    mbar_init(bar + B_SB * 8, 1);
    for (int i = 0; i < 8; i++) mbar_init(bar + (B_ST + i) * 8, 4);
    asm volatile("fence.mbarrier_init.release.cluster;" ::: "memory");
  }
  __syncthreads();
  if (CL) cluster_sync_all();
  asm volatile("griddepcontrol.launch_dependents;" ::: "memory");

  const int wgi = __shfl_sync(0xffffffffu, tid >> 7, 0);
  if (wgi < 2) {
    asm volatile("setmaxnreg.inc.sync.aligned.u32 200;");
    const int wg = wgi, w = warp & 3;
    uint32_t W[112];
    if (wg == 0) tile_prologue<0>(W, sb); else tile_prologue<1>(W, sb);
    named_bar(0, CHAIN_THREADS);
    if (CL) cluster_sync_all();

    const uint32_t stg_base = sb + OFF_A + wg * 4 * STG_BYTES;
    token_gemm(W, sb, 0, stg_base, w, lane);
    token_gemm(W, sb, 1, stg_base, w, lane);
    __syncwarp();
    if (wg == 0 && lane == 0) { mbar_arrive(bar + (B_KR + 0) * 8); mbar_arrive(bar + (B_KR + 1) * 8); }

    if (wg == 0) {
      for (int s = 0; s < NSEG; s++) {
        float d0, d1, d2, d3;
        uint32_t ma[2];
        volatile uint32_t* var = reinterpret_cast<volatile uint32_t*>(smem + OFF_VAR);
        mbar_wait(bar + B_SB * 8, s & 1);
        uint32_t n = var[3];
        const uint32_t n_first = n;
        while (true) {
          const int slot = n & 3;
          mbar_wait(bar + (B_MF + slot) * 8, (n >> 2) & 1);
          if (tid == 0) DBG(0);
          const uint32_t ms = sb + mslot_off(slot);
          float a4[4][4];
#pragma unroll
          for (int i = 0; i < 4; i++) { a4[i][0] = a4[i][1] = a4[i][2] = a4[i][3] = 0.f; }
          uint32_t b[14][4];
#pragma unroll
          for (int i = 0; i < 14; i++) ldsm_x4_t(b[i], ms + (32 * i + lane) * 16);
          ldsm_x2_t(ma, ms + (64 * j + 16 * w + (lane & 15)) * 16);
#pragma unroll
          for (int i = 0; i < 14; i++) {
            mma16816(a4[(2 * i) & 3], W[8 * i + 0], W[8 * i + 1], W[8 * i + 2], W[8 * i + 3], b[i][0], b[i][1]);
            mma16816(a4[(2 * i + 1) & 3], W[8 * i + 4], W[8 * i + 5], W[8 * i + 6], W[8 * i + 7], b[i][2], b[i][3]);
          }
          d0 = (a4[0][0] + a4[1][0]) + (a4[2][0] + a4[3][0]); d1 = (a4[0][1] + a4[1][1]) + (a4[2][1] + a4[3][1]);
          d2 = (a4[0][2] + a4[1][2]) + (a4[2][2] + a4[3][2]); d3 = (a4[0][3] + a4[1][3]) + (a4[2][3] + a4[3][3]);
          if (!__any_sync(~0u, (d0 != d0) | (d1 != d1))) break;
          if (!slot_has_sentinel(smem + mslot_off(slot), lane)) break;
          if (n - n_first > (uint32_t)SPIN_LIMIT) break;
          if (lane == 0) mbar_arrive(bar + (B_EM + slot) * 8);
          n++;
        }
        if (tid == 0) { var[2] = n; var[1] = s; reinterpret_cast<uint32_t*>(smem + OFF_DBG)[s * 16 + 14] = n - n_first; }
        asm volatile("bar.arrive 5, 256;" ::: "memory");
        if (tid == 0) { asm volatile("" :: "f"(d0), "f"(d3)); DBG(8); }
        const uint32_t kb0 = movm_t(pack_bf16(d0, d1)), kb1 = movm_t(pack_bf16(d2, d3));
        if (s < NSEG - 1) {
          float c[4] = {0.f, 0.f, 0.f, 0.f};
          mma16816(c, ma[0], 0u, ma[1], 0u, kb0, kb1);
          float2* sw = reinterpret_cast<float2*>(smem + OFF_SW);
          sw[w * 32 + lane] = make_float2(c[0], c[1]);
          if (tid == 0) DBG(9);
          named_bar(1, 128);
          if (tid == 0) DBG(10);
          if (w == 0) {
            const float2 v0 = sw[lane], v1 = sw[32 + lane], v2 = sw[64 + lane], v3 = sw[96 + lane];
            red_v4(args.Sg + (((size_t)s * NH + h) * 5 + 4) * 32 + lane, (v0.x + v1.x) + (v2.x + v3.x), (v0.y + v1.y) + (v2.y + v3.y), 1.f, 0.f);
          }
        }
        asm volatile("bar.arrive 3, 256;" ::: "memory");
        if (tid == 0) DBG(1);
        {
          const uint32_t stg = stg_base + (s & 3) * STG_BYTES + g * 128 + q * 4;
          asm volatile("st.shared.u32 [%0], %1;" ::"r"(stg + (((2 * w) ^ g) << 4)), "r"(kb0) : "memory");
          asm volatile("st.shared.u32 [%0], %1;" ::"r"(stg + (((2 * w + 1) ^ g) << 4)), "r"(kb1) : "memory");
          fence_async_smem();
          __syncwarp();
          if (lane == 0) mbar_arrive(bar + (B_ST + (s & 3)) * 8);
        }
        if (s + 2 < NSEG) {
          token_gemm(W, sb, s + 2, stg_base, w, lane);
          __syncwarp();
          if (lane == 0) mbar_arrive(bar + (B_KR + ((s + 2) & 3)) * 8);
        }
        if (tid == 0) DBG(11);
        named_bar(1, 128);
      }
    } else {
      const int hd = w * 4 + (lane >> 3);
      uint32_t p_dst = sb + OFF_P + h * 128 + (lane & 7) * 16, p_bar = bar + B_PB * 8;
      if (CL) { p_dst = mapa(p_dst, hd); p_bar = mapa(p_bar, hd); }
      const uint32_t ONE2 = 0x3F803F80u;
      for (int s = 0; s < NSEG; s++) {
        if (s < NSEG - 1) {
          mbar_wait(bar + (B_KR + (s & 3)) * 8, (s >> 2) & 1);
          const uint32_t kst = sb + OFF_A + (s & 3) * STG_BYTES + 1024;
          uint32_t bk[2][4];
#pragma unroll
          for (int i = 0; i < 2; i++) ldsm_x4(bk[i], kst + (8 * w + (lane & 7)) * 128 + (((4 * i + (lane >> 3)) ^ (lane & 7)) << 4));
          float c[4] = {0.f, 0.f, 0.f, 0.f}, c2[4] = {0.f, 0.f, 0.f, 0.f};
          named_bar(5, 256);
          {
            const uint32_t ms = sb + mslot_off(reinterpret_cast<volatile uint32_t*>(smem + OFF_VAR)[2] & 3);
            uint32_t a[2][4];
            ldsm_x4_t(a[0], ms + (64 * j + lane) * 16);
            ldsm_x4_t(a[1], ms + (64 * j + 32 + lane) * 16);
            mma16816(c, a[0][0], 0u, a[0][1], 0u, bk[0][0], bk[0][1]);
            mma16816(c2, a[0][2], 0u, a[0][3], 0u, bk[0][2], bk[0][3]);
            mma16816(c, a[1][0], 0u, a[1][1], 0u, bk[1][0], bk[1][1]);
            mma16816(c2, a[1][2], 0u, a[1][3], 0u, bk[1][2], bk[1][3]);
            c[0] += c2[0]; c[1] += c2[1];
          }
          red_v4(args.Sg + (((size_t)s * NH + h) * 5 + w) * 32 + lane, c[0], c[1], 1.f, 0.f);
        } else named_bar(5, 256);
        named_bar(3, 256);
        const uint32_t ms = sb + mslot_off(reinterpret_cast<volatile uint32_t*>(smem + OFF_VAR)[2] & 3);
        float a4[4][4];
#pragma unroll
        for (int i = 0; i < 4; i++) { a4[i][0] = a4[i][1] = a4[i][2] = a4[i][3] = 0.f; }
        {
          uint32_t b[14][4];
#pragma unroll
          for (int i = 0; i < 14; i++) ldsm_x4_t(b[i], ms + (32 * i + lane) * 16);
#pragma unroll
          for (int i = 0; i < 14; i++) {
            mma16816(a4[(2 * i) & 3], W[8 * i + 0], W[8 * i + 1], W[8 * i + 2], W[8 * i + 3], b[i][0], b[i][1]);
            mma16816(a4[(2 * i + 1) & 3], W[8 * i + 4], W[8 * i + 5], W[8 * i + 6], W[8 * i + 7], b[i][2], b[i][3]);
          }
        }
        const uint32_t za0 = pack_bf16((a4[0][0] + a4[1][0]) + (a4[2][0] + a4[3][0]), (a4[0][1] + a4[1][1]) + (a4[2][1] + a4[3][1]));
        const uint32_t za1 = pack_bf16((a4[0][2] + a4[1][2]) + (a4[2][2] + a4[3][2]), (a4[0][3] + a4[1][3]) + (a4[2][3] + a4[3][3]));
        {
          const uint32_t stg = stg_base + (s & 3) * STG_BYTES + g * 128 + q * 4;
          asm volatile("st.shared.u32 [%0], %1;" ::"r"(stg + (((2 * w) ^ g) << 4)), "r"(movm_t(za0)) : "memory");
          asm volatile("st.shared.u32 [%0], %1;" ::"r"(stg + (((2 * w + 1) ^ g) << 4)), "r"(movm_t(za1)) : "memory");
          fence_async_smem();
          __syncwarp();
          if (lane == 0) mbar_arrive(bar + (B_ST + 4 + (s & 3)) * 8);
        }
        if (s < NSEG - 1) {
          uint32_t va[2][4];
          const uint32_t vst = stg_base + (s & 3) * STG_BYTES + 1024;
#pragma unroll
          for (int kk = 0; kk < 2; kk++) {
            const int mi = lane >> 3, r = lane & 7;
            const int t = 8 * (2 * kk + (mi >> 1)) + r;
            ldsm_x4_t(va[kk], vst + t * 128 + (((2 * w + (mi & 1)) ^ r) << 4));
          }
          mbar_wait(bar + (B_SX + (s & 1)) * 8, (s >> 1) & 1);
          const float2* sx = reinterpret_cast<const float2*>(smem + OFF_SX + (s & 1) * 1024);
          float ex[8];
#pragma unroll
          for (int nt = 0; nt < 4; nt++) { const float2 v = sx[nt * 32 + lane]; ex[2 * nt] = v.x; ex[2 * nt + 1] = v.y; }
          float mx = fmaxf(fmaxf(fmaxf(ex[0], ex[1]), fmaxf(ex[2], ex[3])), fmaxf(fmaxf(ex[4], ex[5]), fmaxf(ex[6], ex[7])));
          mx = fmaxf(mx, __shfl_xor_sync(~0u, mx, 1));
          mx = fmaxf(mx, __shfl_xor_sync(~0u, mx, 2));
#pragma unroll
          for (int k = 0; k < 8; k++) ex[k] = ex2((ex[k] - mx) * L2E);
          mbar_wait(bar + (B_SM + (s & 1)) * 8, (s >> 1) & 1);
          if (tid == 128) DBG(2);
          const float2 sm = reinterpret_cast<const float2*>(smem + OFF_SM + (s & 1) * 256)[lane];
          float mm = fmaxf(sm.x, sm.y);
          mm = fmaxf(mm, __shfl_xor_sync(~0u, mm, 1));
          mm = fmaxf(mm, __shfl_xor_sync(~0u, mm, 2));
          const float m = fmaxf(mx, mm);
          const float f = ex2((mx - m) * L2E);
          const uint32_t pm = pack_bf16(ex2((sm.x - m) * L2E), ex2((sm.y - m) * L2E));
          uint32_t bx[4];
#pragma unroll
          for (int nt = 0; nt < 4; nt++) bx[nt] = pack_bf16(ex[2 * nt] * f, ex[2 * nt + 1] * f);
          float o0[4] = {0.f, 0.f, 0.f, 0.f}, o1[4] = {0.f, 0.f, 0.f, 0.f}, o2[4] = {0.f, 0.f, 0.f, 0.f};
          float l0[4] = {0.f, 0.f, 0.f, 0.f}, l1[4] = {0.f, 0.f, 0.f, 0.f}, l2[4] = {0.f, 0.f, 0.f, 0.f};
          mma1688(o0, za0, za1, pm);
          mma1688(l0, ONE2, ONE2, pm);
          mma16816(o1, va[0][0], va[0][1], va[0][2], va[0][3], bx[0], bx[1]);
          mma16816(l1, ONE2, ONE2, ONE2, ONE2, bx[0], bx[1]);
          mma16816(o2, va[1][0], va[1][1], va[1][2], va[1][3], bx[2], bx[3]);
          mma16816(l2, ONE2, ONE2, ONE2, ONE2, bx[2], bx[3]);
          const float r0 = __fdividef(1.f, l0[0] + l1[0] + l2[0]), r1 = __fdividef(1.f, l0[1] + l1[1] + l2[1]);
          const float v0 = (o0[0] + o1[0] + o2[0]) * r0, v1 = (o0[1] + o1[1] + o2[1]) * r1;
          const float v2 = (o0[2] + o1[2] + o2[2]) * r0, v3 = (o0[3] + o1[3] + o2[3]) * r1;
          if (CL) {
            st_async_v4(p_dst + (s & 1) * 2048, v0, v1, v2, v3, p_bar + (s & 1) * 8);
          } else {
            uint4* dst = reinterpret_cast<uint4*>(args.Sg + (size_t)NSEG * NH * 5 * 32) + ((((size_t)s * NJ + j) * 16 + hd) * 16 + h) * 8 + (lane & 7);
            uint32_t u0 = ~__float_as_uint(v0), u1 = ~__float_as_uint(v1), u2 = ~__float_as_uint(v2), u3 = ~__float_as_uint(v3);
            u0 += (u0 == 0); u1 += (u1 == 0); u2 += (u2 == 0); u3 += (u3 == 0);
            asm volatile("st.relaxed.gpu.global.v4.u32 [%0], {%1,%2,%3,%4};" ::"l"(dst), "r"(u0), "r"(u1), "r"(u2), "r"(u3) : "memory");
          }
          if (tid == 128) DBG(3);
        }
        if (s + 2 < NSEG) token_gemm(W, sb, s + 2, stg_base, w, lane);
        if (tid == 128) DBG(12);
      }
    }
  } else if (wgi == 2) {
    asm volatile("setmaxnreg.dec.sync.aligned.u32 80;");
    const int aw = warp - 8, at = tid - 256;
    named_bar(0, CHAIN_THREADS);
    if (CL) cluster_sync_all();
    for (int s = 0; s < NSEG; s++) {
      volatile uint32_t* var = reinterpret_cast<volatile uint32_t*>(smem + OFF_VAR);
      { int it = 0; while (var[1] != (uint32_t)s && ++it < SPIN_LIMIT) __nanosleep(20); }
      if (at == 32) DBG(4);
      if (s == NSEG - 1) break;
      const uint32_t tM = clk32();
      {
        const float4* src = args.Sg + (((size_t)s * NH + h) * 5 + aw) * 32 + lane;
        while ((int)(clk32() - tM) < SXSTART) {}
        uint4 v; int it = 0;
        do { v = ld_vol_v4(src); } while (__uint_as_float(v.z) != 7.f && ++it < SPIN_LIMIT);
        reinterpret_cast<float2*>(smem + OFF_SX + (s & 1) * 1024)[aw * 32 + lane] = make_float2(__uint_as_float(v.x), __uint_as_float(v.y));
        __syncwarp();
        if (lane == 0) mbar_arrive(bar + (B_SX + (s & 1)) * 8);
        if (at == 0) DBG(13);
      }
    }
  } else {
    asm volatile("setmaxnreg.dec.sync.aligned.u32 32;");
    if (tid == 384) {
      reinterpret_cast<uint32_t*>(smem + OFF_VAR)[0] = 0; reinterpret_cast<uint32_t*>(smem + OFF_VAR)[1] = ~0u;
      issue_x_load<CL>(sb, &tm_x, 0, h);
      issue_x_load<CL>(sb, &tm_x, 1, h);
      mbar_expect_tx(bar + B_PA * 8, 65536);
#pragma unroll
      for (int ec = 0; ec < 4; ec++) tma_load_2d(sb + OFF_A + ec * 8192, &tm_wq, h * DH + ec * 64, 64 * j, bar + B_PA * 8);
      tma_load_2d(sb + OFF_A + 32768, &tm_wo, 64 * j, h * DH, bar + B_PA * 8);
      for (int i = 0; i < 16; i++) {
        const int st = i % 3, half = i >> 3, ec = (i & 7) >> 1;
        if (i >= 3) mbar_wait(bar + (B_PE + st) * 8, ((i / 3) - 1) & 1);
        mbar_expect_tx(bar + (B_PF + i) * 8, XT_BYTES);
        tma_load_2d(sb + OFF_B + st * XT_BYTES, (i & 1) ? &tm_wv : &tm_wk, h * DH + ec * 64, half * 224, bar + (B_PF + i) * 8);
      }
    }
    __syncwarp();
    named_bar(0, CHAIN_THREADS);
    if (CL) cluster_sync_all();
    if (tid == 384) {
      issue_x_load<CL>(sb, &tm_x, 2, h); issue_x_load<CL>(sb, &tm_x, 3, h);
      for (int s = 0; s < NSEG; s++) {
        mbar_wait(bar + (B_ST + (s & 3)) * 8, (s >> 2) & 1);
        tma_store_2d(&tm_k, 64 * j, (h * NSEG + s) * LKEY, sb + OFF_A + (s & 3) * STG_BYTES);
        mbar_wait(bar + (B_ST + 4 + (s & 3)) * 8, (s >> 2) & 1);
        tma_store_2d(&tm_y, 64 * j, (h * NSEG + s) * LKEY, sb + OFF_A + (4 + (s & 3)) * STG_BYTES);
        bulk_commit();
        if (s + 4 < NSEG) issue_x_load<CL>(sb, &tm_x, s + 4, h);
        bulk_wait<0>();
        fence_async_all();
        __threadfence();
        red_u32(args.flag + s, 1u);
      }
    } else if (warp == 13) {
      {
        const int l8 = lane >> 2, v = lane & 3;
        const int c = 16 * (h >> 2) + 2 * (h & 3) + (l8 >> 2) + (v >> 1) * 8, i = 2 * (l8 & 3);
        const uint16_t* m0 = reinterpret_cast<const uint16_t*>(args.mem0);
        uint32_t u = (uint32_t)m0[i * DM + 64 * j + c] | ((uint32_t)m0[(i + 1) * DM + 64 * j + c] << 16);
        if ((u & 0xFFFFu) == 0xFFFFu) u &= ~0x8000u;
        if ((u >> 16) == 0xFFFFu) u &= ~0x80000000u;
        if (!(lane & 1)) st_relaxed(args.Mg + (64 * j + c) * 4 + (l8 & 3), u);
      }
      for (int s = 0; s < NSEG - 1; s++) {
        float acc;
        if (CL && lane == 0) mbar_expect_tx(bar + (B_PB + (s & 1)) * 8, 16 * 128);
        poll_smm(smem, bar, args.Sg + (((size_t)s * NH + h) * 5 + 4) * 32 + lane, s, 1, lane);
        if (CL) {
          mbar_wait_cluster(bar + (B_PB + (s & 1)) * 8, (s >> 1) & 1);
          if (lane == 0) DBG(5);
          const float* pin = reinterpret_cast<const float*>(smem + OFF_P + (s & 1) * 2048);
          float a0 = 0.f, a1 = 0.f, a2 = 0.f, a3 = 0.f;
#pragma unroll
          for (int k = 0; k < 16; k += 4) { a0 += pin[k * 32 + lane]; a1 += pin[(k + 1) * 32 + lane]; a2 += pin[(k + 2) * 32 + lane]; a3 += pin[(k + 3) * 32 + lane]; }
          acc = (a0 + a1) + (a2 + a3);
        } else {
          const uint32_t* src = reinterpret_cast<const uint32_t*>(args.Sg + (size_t)NSEG * NH * 5 * 32) + (((size_t)s * NJ + j) * 16 + h) * 16 * 32 + lane;
          acc = 0.f;
#pragma unroll 1
          for (int k = 0; k < 16; k += 4) {
            uint32_t v0, v1, v2, v3; int it = 0;
            do {
              asm volatile("ld.volatile.global.u32 %0, [%1];" : "=r"(v0) : "l"(src + k * 32) : "memory");
              asm volatile("ld.volatile.global.u32 %0, [%1];" : "=r"(v1) : "l"(src + k * 32 + 32) : "memory");
              asm volatile("ld.volatile.global.u32 %0, [%1];" : "=r"(v2) : "l"(src + k * 32 + 64) : "memory");
              asm volatile("ld.volatile.global.u32 %0, [%1];" : "=r"(v3) : "l"(src + k * 32 + 96) : "memory");
            } while ((v0 == 0u || v1 == 0u || v2 == 0u || v3 == 0u) && ++it < SPIN_LIMIT);
            acc += (__uint_as_float(~v0) + __uint_as_float(~v1)) + (__uint_as_float(~v2) + __uint_as_float(~v3));
          }
        }
        const float o = __shfl_down_sync(~0u, acc, 1);
        const uint32_t u = pack_bf16(acc, o);
        const int l8 = lane >> 2, v = lane & 3;
        const int c = 16 * (h >> 2) + 2 * (h & 3) + (l8 >> 2) + (v >> 1) * 8;
        if (!(lane & 1)) st_relaxed(args.Mg + (size_t)(s + 1) * 1792 + (64 * j + c) * 4 + (l8 & 3), u);
        if (lane == 0) { DBG(6); mbar_arrive(bar + (B_RD + (s & 1)) * 8); }
      }
    } else if (warp == 15) {
      for (int s = 0; s < NSEG - 1; s++) poll_smm(smem, bar, args.Sg + (((size_t)s * NH + h) * 5 + 4) * 32 + lane, s, 0, lane);
    } else if (tid == 448) {
      volatile uint32_t* var = reinterpret_cast<volatile uint32_t*>(smem + OFF_VAR);
      uint32_t n = 0, empar = 0;
      for (int s = 0; s < NSEG; s++) {
        if (s > 0) mbar_wait(bar + (B_RD + ((s - 1) & 1)) * 8, ((s - 1) >> 1) & 1);
        const uint32_t n0 = n;
        var[3] = n0;
        mbar_arrive(bar + B_SB * 8);
        uint32_t tnext = clk32() + MD0;
        int it = 0;
        while (true) {
          bool done = false;
          while ((int)(clk32() - tnext) < 0) { if (var[1] == (uint32_t)s) { done = true; break; } }
          if (done || var[1] == (uint32_t)s || ++it > SPIN_LIMIT) break;
          const int slot = n & 3;
          if (n - n0 >= 4) {
            int it2 = 0;
            while (!mbar_test(bar + (B_EM + slot) * 8, (empar >> slot) & 1)) { if (var[1] == (uint32_t)s || ++it2 > SPIN_LIMIT) { done = true; break; } }
            if (done) break;
            empar ^= 1u << slot;
          }
          mbar_expect_tx(bar + (B_MF + slot) * 8, 7168);
          bulk_load(sb + mslot_off(slot), args.Mg + (size_t)s * 1792, 7168, bar + (B_MF + slot) * 8);
          n++;
          tnext += MDELTA;
        }
        const uint32_t ns = var[2];
        const uint32_t waited = n - n0 > 4 ? n - n0 - 4 : 0;
        for (uint32_t a = n0 + waited; a < ns; a++) empar ^= 1u << (a & 3);
        for (uint32_t a = ns + 1; a < n; a++) mbar_wait(bar + (B_MF + (a & 3)) * 8, (a >> 2) & 1);
        reinterpret_cast<uint32_t*>(smem + OFF_DBG)[s * 16 + 15] = n - n0;
      }
    }
    __syncwarp();
  }
  named_bar(0, CHAIN_THREADS);
  if (CL) cluster_sync_all();
}
struct SsmArgs {
  const bf16 *lam_re, *lam_im, *log_dt, *dskip, *x, *gate_w;
  float* hloc;
  float2* hend;
  float* omg;
  float* out;
};

__device__ __forceinline__ float bf2f(bf16 v) { return __bfloat162float(v); }
__device__ __forceinline__ float rbf(float v) { return __bfloat162float(__float2bfloat16_rn(v)); }
__device__ __forceinline__ float2 cmul(float2 a, float2 b) { return make_float2(a.x * b.x - a.y * b.y, a.x * b.y + a.y * b.x); }
__device__ __forceinline__ float2 ssm_z(const SsmArgs& a, int ch) {
  const float dt = rbf(expf(bf2f(a.log_dt[ch])));
  return make_float2(dt * bf2f(a.lam_re[ch]), dt * bf2f(a.lam_im[ch]));
}
__device__ __forceinline__ float2 cexp_n(float2 z, float n) {
  float sn, cs;
  sincosf(z.y * n, &sn, &cs);
  const float e = expf(z.x * n);
  return make_float2(e * cs, e * sn);
}

constexpr int S1_STAGE = 32768, S1_NST = 4, S1_SMEM = S1_NST * S1_STAGE + 256;
__global__ void __launch_bounds__(160, 1)
ssm1_kernel(const __grid_constant__ CUtensorMap tm_bre, const __grid_constant__ CUtensorMap tm_bim, const __grid_constant__ CUtensorMap tm_xp, SsmArgs args) {
  extern __shared__ __align__(1024) uint8_t smem[];
  const uint32_t sb = smem_u32(smem), bar = sb + S1_NST * S1_STAGE;
  const int tid = threadIdx.x, warp = tid >> 5, lane = tid & 31;
  const int cg = blockIdx.x, tc = blockIdx.y;
  if (tid == 0) {
    for (int i = 0; i < 7; i++) mbar_init(bar + i * 8, 1);
    for (int i = 0; i < 4; i++) mbar_init(bar + (8 + i) * 8, 4);
    asm volatile("fence.mbarrier_init.release.cluster;" ::: "memory");
  }
  __syncthreads();
  if (warp == 4) {
    if (lane == 0) {
      for (int kc = 0; kc < 7; kc++) {
        const int st = kc & 3;
        if (kc >= 4) mbar_wait(bar + (8 + st) * 8, 0);
        mbar_expect_tx(bar + kc * 8, S1_STAGE);
        tma_load_2d(sb + st * S1_STAGE, &tm_bre, kc * 64, cg * 64, bar + kc * 8);
        tma_load_2d(sb + st * S1_STAGE + 8192, &tm_bim, kc * 64, cg * 64, bar + kc * 8);
        tma_load_4d(sb + st * S1_STAGE + 16384, &tm_xp, kc * 64, 0, tc * 4, 0, bar + kc * 8);
      }
    }
    return;
  }
  float ur[64], ui[64];
#pragma unroll 1
  for (int kc = 0; kc < 7; kc++) {
    const int st = kc & 3;
    mbar_wait(bar + kc * 8, 0);
    const uint32_t b0 = sb + st * S1_STAGE;
    wg_fence();
#pragma unroll
    for (int kk = 0; kk < 4; kk++) {
      wgmma_ss_n128(ur, desc_sw128(b0 + kk * 32), desc_sw128(b0 + 16384 + kk * 32), (kc | kk) != 0);
      wgmma_ss_n128(ui, desc_sw128(b0 + 8192 + kk * 32), desc_sw128(b0 + 16384 + kk * 32), (kc | kk) != 0);
    }
    wg_commit();
    wg_wait<0>();
    if (lane == 0) mbar_arrive(bar + (8 + st) * 8);
  }
  const int g = lane >> 2, q = lane & 3;
#pragma unroll
  for (int r = 0; r < 2; r++) {
    const int ch = cg * 64 + warp * 16 + g + r * 8;
    const float2 z = ssm_z(args, ch);
    const float2 lam = cexp_n(z, 1.f);
    const float lr = bf2f(args.lam_re[ch]), li = bf2f(args.lam_im[ch]);
    const float den = lr * lr + li * li;
    const float2 num = make_float2(lam.x - 1.f, lam.y);
    const float2 coef = make_float2((num.x * lr + num.y * li) / den, (num.y * lr - num.x * li) / den);
    float2 hs = make_float2(0.f, 0.f);
#pragma unroll
    for (int i = 0; i < 32; i++) {
      const int idx = (i >> 1) * 4 + r * 2 + (i & 1);
      const float2 bu = cmul(coef, make_float2(ur[idx], ui[idx]));
      hs = make_float2(fmaf(lam.x, hs.x, fmaf(-lam.y, hs.y, bu.x)), fmaf(lam.x, hs.y, fmaf(lam.y, hs.x, bu.y)));
      ur[idx] = hs.x; ui[idx] = hs.y;
    }
    const float2 l32 = cexp_n(z, 32.f);
    float2 carry = make_float2(0.f, 0.f);
#pragma unroll
    for (int qq = 0; qq < 3; qq++) {
      const float ex = __shfl_sync(~0u, hs.x, (lane & ~3) + qq), ey = __shfl_sync(~0u, hs.y, (lane & ~3) + qq);
      if (qq < q) { const float2 t = cmul(l32, carry); carry = make_float2(t.x + ex, t.y + ey); }
    }
    float2 p = lam;
    float* dre = args.hloc + (size_t)ch * SEQ + tc * 128 + q * 32;
    float* dim = dre + (size_t)DM * SEQ;
#pragma unroll
    for (int i4 = 0; i4 < 8; i4++) {
      float vr[4], vi[4];
#pragma unroll
      for (int e = 0; e < 4; e++) {
        const int i = i4 * 4 + e, idx = (i >> 1) * 4 + r * 2 + (i & 1);
        const float2 t = cmul(p, carry);
        vr[e] = ur[idx] + t.x; vi[e] = ui[idx] + t.y;
        p = cmul(p, lam);
      }
      *reinterpret_cast<float4*>(dre + i4 * 4) = make_float4(vr[0], vr[1], vr[2], vr[3]);
      *reinterpret_cast<float4*>(dim + i4 * 4) = make_float4(vi[0], vi[1], vi[2], vi[3]);
      if (i4 == 7 && q == 3) args.hend[tc * DM + ch] = make_float2(vr[3], vi[3]);
    }
  }
}

constexpr int S2_A = 896 * 128, S2_NST = 3, S2_SMEM = S2_A + S2_NST * XT_BYTES + 1024;
__global__ void __launch_bounds__(288, 1)
ssm2_kernel(const __grid_constant__ CUtensorMap tm_cre, const __grid_constant__ CUtensorMap tm_cim, SsmArgs args) {
  extern __shared__ __align__(1024) uint8_t smem[];
  const uint32_t sb = smem_u32(smem), bar = sb + S2_A + S2_NST * XT_BYTES;
  float* sg = reinterpret_cast<float*>(smem + S2_A + S2_NST * XT_BYTES + 512);
  const int tid = threadIdx.x, warp = tid >> 5, lane = tid & 31;
  const int t0 = blockIdx.x * 64, chunk = t0 >> 7, tau0 = t0 & 127;
  if (tid == 0) {
    for (int i = 0; i < 28; i++) mbar_init(bar + i * 8, 1);
    for (int i = 0; i < 3; i++) mbar_init(bar + (28 + i) * 8, 4);
    asm volatile("fence.mbarrier_init.release.cluster;" ::: "memory");
  }
  __syncthreads();
  if (warp == 8) {
    if (lane == 0) {
      for (int i = 0; i < 28; i++) {
        const int st = i % 3, kc = i >> 1;
        if (i >= 3) mbar_wait(bar + (28 + st) * 8, ((i / 3) - 1) & 1);
        mbar_expect_tx(bar + i * 8, XT_BYTES);
        tma_load_2d(sb + S2_A + st * XT_BYTES, kc < 7 ? &tm_cre : &tm_cim, (kc % 7) * 64, (i & 1) * 224, bar + i * 8);
      }
    }
    return;
  }
  for (int tt = 0; tt < 8; tt++) {
    const int t = t0 + warp * 8 + tt;
    float acc = 0.f;
    for (int d = lane; d < DM; d += 32) acc += rbf(bf2f(args.x[(size_t)t * DM + d]) * bf2f(args.gate_w[d]));
#pragma unroll
    for (int o = 16; o; o >>= 1) acc += __shfl_xor_sync(~0u, acc, o);
    if (lane == 0) {
      const float gv = rbf(1.f / (1.f + expf(-rbf(acc))));
      sg[warp * 8 + tt] = gv;
      args.omg[t] = rbf(1.f - gv);
    }
  }
  for (int it = tid; it < DM * 8; it += 256) {
    const int ch = it >> 3, m8 = it & 7;
    const float2 z = ssm_z(args, ch);
    float2 hin = make_float2(0.f, 0.f);
    if (chunk > 0) {
      const float2 l128 = cexp_n(z, 128.f);
      for (int c = 0; c < chunk; c++) { const float2 e = args.hend[c * DM + ch], t = cmul(l128, hin); hin = make_float2(t.x + e.x, t.y + e.y); }
    }
    const float2 lam = cexp_n(z, 1.f);
    float2 p = cmul(cexp_n(z, (float)(tau0 + m8 * 8 + 1)), hin);
    const float* sre = args.hloc + (size_t)ch * SEQ + t0 + m8 * 8;
    const float* sim = sre + (size_t)DM * SEQ;
    const float4 r0 = *reinterpret_cast<const float4*>(sre), r1 = *reinterpret_cast<const float4*>(sre + 4);
    const float4 i0 = *reinterpret_cast<const float4*>(sim), i1 = *reinterpret_cast<const float4*>(sim + 4);
    float vr[8] = {r0.x, r0.y, r0.z, r0.w, r1.x, r1.y, r1.z, r1.w}, vi[8] = {i0.x, i0.y, i0.z, i0.w, i1.x, i1.y, i1.z, i1.w};
#pragma unroll
    for (int e = 0; e < 8; e++) { vr[e] = 2.f * (vr[e] + p.x); vi[e] = -2.f * (vi[e] + p.y); p = cmul(p, lam); }
    const uint4 pr = make_uint4(pack_bf16(vr[0], vr[1]), pack_bf16(vr[2], vr[3]), pack_bf16(vr[4], vr[5]), pack_bf16(vr[6], vr[7]));
    const uint4 pi = make_uint4(pack_bf16(vi[0], vi[1]), pack_bf16(vi[2], vi[3]), pack_bf16(vi[4], vi[5]), pack_bf16(vi[6], vi[7]));
    *reinterpret_cast<uint4*>(smem + ch * 128 + ((m8 ^ (ch & 7)) << 4)) = pr;
    *reinterpret_cast<uint4*>(smem + (DM + ch) * 128 + ((m8 ^ (ch & 7)) << 4)) = pi;
  }
  fence_async_smem();
  named_bar(1, 256);
  const int wg = warp >> 2, w = warp & 3;
  float acc[112];
#pragma unroll 1
  for (int kc = 0; kc < 14; kc++) {
    const int i = kc * 2 + wg, st = i % 3;
    mbar_wait(bar + i * 8, 0);
    const uint32_t bb = sb + S2_A + st * XT_BYTES;
    wg_fence();
#pragma unroll
    for (int kk = 0; kk < 4; kk++) {
      const uint64_t da = desc_sw128(sb + (kc * 64 + kk * 16) * 128);
      wgmma_ss_n112_ta(acc, da, desc_sw128(bb + kk * 32), (kc | kk) != 0);
      wgmma_ss_n112_ta(acc + 56, da, desc_sw128(bb + 14336 + kk * 32), (kc | kk) != 0);
    }
    wg_commit();
    wg_wait<0>();
    if (lane == 0) mbar_arrive(bar + (28 + st) * 8);
  }
  const int g = lane >> 2, q = lane & 3;
#pragma unroll
  for (int r = 0; r < 2; r++) {
    const int tl = w * 16 + g + r * 8, t = t0 + tl;
    const float gv = sg[tl];
#pragma unroll
    for (int nt = 0; nt < 28; nt++) {
      const int d = wg * 224 + nt * 8 + 2 * q;
      const __nv_bfloat162 xv = *reinterpret_cast<const __nv_bfloat162*>(args.x + (size_t)t * DM + d);
      const __nv_bfloat162 dv = *reinterpret_cast<const __nv_bfloat162*>(args.dskip + d);
      const float a0 = acc[nt * 4 + r * 2] + rbf(bf2f(xv.x) * bf2f(dv.x)), a1 = acc[nt * 4 + r * 2 + 1] + rbf(bf2f(xv.y) * bf2f(dv.y));
      *reinterpret_cast<float2*>(args.out + (size_t)t * DM + d) = make_float2(gv * a0, gv * a1);
    }
  }
}
struct AttnArgs {
  const uint32_t* flag;
  uint32_t* ticket;
  const float* omg;
  float* out;
};
constexpr int AT_G = 2, AT_ITEMS = NSEG * (NH / AT_G);
constexpr int AT_X = 7 * 8192;
constexpr int AT_K = 7 * 5120, AT_Y = 7 * 6144, AT_HEAD = AT_K + AT_Y;
constexpr int AT_SMEM = AT_X + 2 * AT_HEAD + 256;
constexpr uint32_t FLAG_TARGET = 112;

template <int NCH, int C0>
__device__ __forceinline__ void attn_consumer(uint32_t sb, uint32_t bar, volatile int* s_item, const AttnArgs& args, int w, int lane) {
  const int g = lane >> 2, q = lane & 3;
  for (int n = 0;; n++) {
    mbar_wait(bar + 24, n & 1);
    const int item = *s_item;
    if (item >= AT_ITEMS) break;
    const int s = item / (NH / AT_G);
    float acc[NCH][32];
    mbar_wait(bar, n & 1);
#pragma unroll
    for (int hh = 0; hh < AT_G; hh++) {
      const uint32_t base = sb + AT_X + hh * AT_HEAD;
      mbar_wait(bar + 8 + hh * 8, n & 1);
      float sc[20];
      wg_fence();
#pragma unroll
      for (int kk = 0; kk < 28; kk++)
        wgmma_ss_n40(sc, desc_sw128(sb + (kk >> 2) * 8192 + (kk & 3) * 32), desc_sw128(base + (kk >> 2) * 5120 + (kk & 3) * 32), kk != 0);
      wg_commit();
      wg_wait<0>();
      uint32_t pa[3][4];
#pragma unroll
      for (int r = 0; r < 2; r++) {
        const int t = w * 16 + g + r * 8;
        float v[10];
        float m = -3.0e38f;
#pragma unroll
        for (int nt = 0; nt < 5; nt++)
#pragma unroll
          for (int e = 0; e < 2; e++) {
            const int key = nt * 8 + 2 * q + e;
            const float x = (key - NMEM <= t) ? sc[nt * 4 + r * 2 + e] : -1.0e9f;
            v[nt * 2 + e] = x; m = fmaxf(m, x);
          }
        m = fmaxf(m, __shfl_xor_sync(~0u, m, 1));
        m = fmaxf(m, __shfl_xor_sync(~0u, m, 2));
        float l = 0.f;
#pragma unroll
        for (int k = 0; k < 10; k++) { v[k] = ex2((v[k] - m) * L2E); l += v[k]; }
        l += __shfl_xor_sync(~0u, l, 1);
        l += __shfl_xor_sync(~0u, l, 2);
        const float rl = w < 2 ? 1.f / l : 0.f;
        pa[0][r] = pack_bf16(v[0] * rl, v[1] * rl); pa[0][2 + r] = pack_bf16(v[2] * rl, v[3] * rl);
        pa[1][r] = pack_bf16(v[4] * rl, v[5] * rl); pa[1][2 + r] = pack_bf16(v[6] * rl, v[7] * rl);
        pa[2][r] = pack_bf16(v[8] * rl, v[9] * rl); pa[2][2 + r] = 0u;
      }
      wg_fence();
#pragma unroll
      for (int c = 0; c < NCH; c++)
#pragma unroll
        for (int kk = 0; kk < 3; kk++)
          wgmma_rs_n64_tb(acc[c], pa[kk], desc_sw128(base + AT_K + (C0 + c) * 6144 + kk * 2048), (hh | kk) != 0);
      wg_commit();
      wg_wait<0>();
    }
    __syncwarp();
    if (lane == 0) mbar_arrive(bar + 32);
    if (w < 2) {
#pragma unroll
      for (int r = 0; r < 2; r++) {
        const int t = s * SEG + w * 16 + g + r * 8;
        const float om = args.omg[t];
        float* dst = args.out + (size_t)t * DM + C0 * 64 + 2 * q;
#pragma unroll
        for (int c = 0; c < NCH; c++)
#pragma unroll
          for (int nt = 0; nt < 8; nt++) red_v2(dst + c * 64 + nt * 8, om * acc[c][nt * 4 + r * 2], om * acc[c][nt * 4 + r * 2 + 1]);
      }
    }
  }
}

__global__ void __launch_bounds__(384, 1)
attn_kernel(const __grid_constant__ CUtensorMap tm_x64, const __grid_constant__ CUtensorMap tm_k, const __grid_constant__ CUtensorMap tm_y, AttnArgs args) {
  extern __shared__ __align__(1024) uint8_t smem[];
  const uint32_t sb = smem_u32(smem), bar = sb + AT_X + 2 * AT_HEAD;
  volatile int* s_item = reinterpret_cast<volatile int*>(smem + AT_X + 2 * AT_HEAD + 128);
  const int tid = threadIdx.x, warp = tid >> 5, lane = tid & 31;
  if (tid == 0) {
    mbar_init(bar, 1); mbar_init(bar + 8, 1); mbar_init(bar + 16, 1); mbar_init(bar + 24, 1); mbar_init(bar + 32, 8);
    asm volatile("fence.mbarrier_init.release.cluster;" ::: "memory");
  }
  for (int i = tid; i < 2 * 7 * 64; i += 384) {
    const int hh = i / (7 * 64), r = i % (7 * 64), c = r >> 6, o = r & 63;
    *reinterpret_cast<uint4*>(smem + AT_X + hh * AT_HEAD + AT_K + c * 6144 + 5120 + o * 16) = make_uint4(0, 0, 0, 0);
  }
  fence_async_smem();
  __syncthreads();
  const int wg = __shfl_sync(0xffffffffu, warp >> 2, 0);
  if (wg == 2) {
    asm volatile("setmaxnreg.dec.sync.aligned.u32 40;");
    if (tid == 256) {
      for (int n = 0;; n++) {
        if (n > 0) mbar_wait(bar + 32, (n - 1) & 1);
        const int item = (int)atomicAdd(args.ticket, 1u);
        *s_item = item;
        mbar_arrive(bar + 24);
        if (item >= AT_ITEMS) break;
        const int s = item / (NH / AT_G), h0 = (item % (NH / AT_G)) * AT_G;
        mbar_expect_tx(bar, AT_X);
#pragma unroll
        for (int c = 0; c < 7; c++) tma_load_2d(sb + c * 8192, &tm_x64, c * 64, s * SEG, bar);
        { int it = 0; while (ld_acquire(args.flag + s) < FLAG_TARGET && ++it < SPIN_LIMIT) __nanosleep(100); }
        fence_async_all();
#pragma unroll
        for (int hh = 0; hh < AT_G; hh++) {
          const uint32_t base = sb + AT_X + hh * AT_HEAD, fb = bar + 8 + hh * 8;
          mbar_expect_tx(fb, 2 * AT_K);
          const int row = ((h0 + hh) * NSEG + s) * LKEY;
#pragma unroll
          for (int c = 0; c < 7; c++) tma_load_2d(base + c * 5120, &tm_k, c * 64, row, fb);
#pragma unroll
          for (int c = 0; c < 7; c++) tma_load_2d(base + AT_K + c * 6144, &tm_y, c * 64, row, fb);
        }
      }
    }
  } else {
    asm volatile("setmaxnreg.inc.sync.aligned.u32 232;");
    if (wg == 0) attn_consumer<4, 0>(sb, bar, s_item, args, warp & 3, lane);
    else attn_consumer<3, 4>(sb, bar, s_item, args, warp & 3, lane);
  }
}
__device__ bf16 g_Kall[(size_t)NH * NSEG * LKEY * DM];
__device__ bf16 g_Yall[(size_t)NH * NSEG * LKEY * DM];
__device__ uint32_t g_M[65 * 1792];
__device__ float4 g_S[(size_t)NSEG * NH * 5 * 32 + (size_t)NSEG * NJ * 16 * 16 * 8];
__device__ uint32_t g_flag[NSEG + 64];
__device__ float g_hloc[2 * DM * SEQ];
__device__ float2 g_hend[16 * DM];
__device__ float g_omg[SEQ];
__device__ uint32_t g_dbg[112 * 1024 + 112 * 4];

typedef CUresult (*EncodeFn)(CUtensorMap*, CUtensorMapDataType, cuuint32_t, void*, const cuuint64_t*, const cuuint64_t*, const cuuint32_t*,
                             const cuuint32_t*, CUtensorMapInterleave, CUtensorMapSwizzle, CUtensorMapL2promotion, CUtensorMapFloatOOBfill);

static bool make_map_2d(EncodeFn enc, CUtensorMap* m, const void* ptr, uint64_t cols, uint64_t rows, uint32_t box_cols, uint32_t box_rows) {
  cuuint64_t dims[2] = {cols, rows};
  cuuint64_t strides[1] = {cols * 2};
  cuuint32_t box[2] = {box_cols, box_rows};
  cuuint32_t es[2] = {1, 1};
  return enc(m, CU_TENSOR_MAP_DATA_TYPE_BFLOAT16, 2, const_cast<void*>(ptr), dims, strides, box, es, CU_TENSOR_MAP_INTERLEAVE_NONE,
             CU_TENSOR_MAP_SWIZZLE_128B, CU_TENSOR_MAP_L2_PROMOTION_L2_256B, CU_TENSOR_MAP_FLOAT_OOB_FILL_NONE) == CUDA_SUCCESS;
}
static bool make_map_xperm(EncodeFn enc, CUtensorMap* m, const void* ptr) {
  cuuint64_t dims[4] = {(cuuint64_t)DM, 2, 64, 16};
  cuuint64_t strides[3] = {(cuuint64_t)DM * 2, (cuuint64_t)DM * 2 * 32, (cuuint64_t)DM * 2 * 2};
  cuuint32_t box[4] = {64, 2, 4, 16};
  cuuint32_t es[4] = {1, 1, 1, 1};
  return enc(m, CU_TENSOR_MAP_DATA_TYPE_BFLOAT16, 4, const_cast<void*>(ptr), dims, strides, box, es, CU_TENSOR_MAP_INTERLEAVE_NONE,
             CU_TENSOR_MAP_SWIZZLE_128B, CU_TENSOR_MAP_L2_PROMOTION_L2_256B, CU_TENSOR_MAP_FLOAT_OOB_FILL_NONE) == CUDA_SUCCESS;
}

struct HostState {
  bool init, ok, use_cluster;
  CUtensorMap tx, tq, tk, tv, to, tka, tya, tbre, tbim, txp, tcre, tcim, tx64;
  void *pK, *pY, *pM, *pS, *pF, *pD, *pH, *pE, *pO;
  cudaStream_t side;
  cudaEvent_t ev_start, ev_join;
  int n_free;
  const void* key[17];
  void* key_out;
};
static HostState g_hs;

}

extern "C" void kernel_launch(void* const* d_in, const int* in_sizes, int n_in, void* d_out, int out_size) {
  HostState& S = g_hs;
  (void)in_sizes; (void)n_in; (void)out_size;
  cudaStream_t st = cudaStreamPerThread;
  bool same = S.init;
  for (int i = 0; i < 17 && same; i++) same = S.key[i] == d_in[i];
  if (!same) {
    EncodeFn enc = nullptr;
    cudaDriverEntryPointQueryResult qr;
    cudaGetDriverEntryPoint("cuTensorMapEncodeTiled", (void**)&enc, cudaEnableDefault, &qr);
    cudaGetSymbolAddress(&S.pK, g_Kall); cudaGetSymbolAddress(&S.pY, g_Yall); cudaGetSymbolAddress(&S.pM, g_M); cudaGetSymbolAddress(&S.pS, g_S);
    cudaGetSymbolAddress(&S.pF, g_flag); cudaGetSymbolAddress(&S.pD, g_dbg); cudaGetSymbolAddress(&S.pH, g_hloc); cudaGetSymbolAddress(&S.pE, g_hend);
    cudaGetSymbolAddress(&S.pO, g_omg);
    S.ok = enc && make_map_2d(enc, &S.tx, d_in[0], DM, SEQ, 64, 32) && make_map_2d(enc, &S.tq, d_in[11], 4096, DM, 64, 64) &&
           make_map_2d(enc, &S.tk, d_in[12], 4096, DM, 64, 224) && make_map_2d(enc, &S.tv, d_in[13], 4096, DM, 64, 224) &&
           make_map_2d(enc, &S.to, d_in[14], DM, 4096, 64, 256) && make_map_2d(enc, &S.tka, S.pK, DM, NH * NSEG * LKEY, 64, LKEY) &&
           make_map_2d(enc, &S.tya, S.pY, DM, NH * NSEG * LKEY, 64, LKEY) && make_map_2d(enc, &S.tbre, d_in[3], DM, DM, 64, 64) &&
           make_map_2d(enc, &S.tbim, d_in[4], DM, DM, 64, 64) && make_map_xperm(enc, &S.txp, d_in[0]) &&
           make_map_2d(enc, &S.tcre, d_in[5], DM, DM, 64, 224) && make_map_2d(enc, &S.tcim, d_in[6], DM, DM, 64, 224) &&
           make_map_2d(enc, &S.tx64, d_in[0], DM, SEQ, 64, 64);
    if (!S.init) {
      cudaFuncSetAttribute(chain_kernel<true>, cudaFuncAttributeMaxDynamicSharedMemorySize, SMEM_CHAIN);
      cudaFuncSetAttribute(chain_kernel<true>, cudaFuncAttributeNonPortableClusterSizeAllowed, 1);
      cudaFuncSetAttribute(chain_kernel<false>, cudaFuncAttributeMaxDynamicSharedMemorySize, SMEM_CHAIN);
      cudaFuncSetAttribute(ssm1_kernel, cudaFuncAttributeMaxDynamicSharedMemorySize, S1_SMEM);
      cudaFuncSetAttribute(ssm2_kernel, cudaFuncAttributeMaxDynamicSharedMemorySize, S2_SMEM);
      cudaFuncSetAttribute(attn_kernel, cudaFuncAttributeMaxDynamicSharedMemorySize, AT_SMEM);
      cudaLaunchConfig_t cfg = {};
      cfg.gridDim = dim3(112); cfg.blockDim = dim3(CHAIN_THREADS); cfg.dynamicSmemBytes = SMEM_CHAIN;
      cudaLaunchAttribute at[1];
      at[0].id = cudaLaunchAttributeClusterDimension; at[0].val.clusterDim.x = 16; at[0].val.clusterDim.y = 1; at[0].val.clusterDim.z = 1;
      cfg.attrs = at; cfg.numAttrs = 1;
      int nc = 0;
      if (cudaOccupancyMaxActiveClusters(&nc, chain_kernel<true>, &cfg) != cudaSuccess) { nc = 0; (void)cudaGetLastError(); }
      S.use_cluster = nc >= 7;
      int sms = 132;
      cudaDeviceGetAttribute(&sms, cudaDevAttrMultiProcessorCount, 0);
      S.n_free = sms - 112 > 1 ? sms - 112 : 1;
      cudaStreamCreateWithFlags(&S.side, cudaStreamNonBlocking);
      cudaEventCreateWithFlags(&S.ev_start, cudaEventDisableTiming);
      cudaEventCreateWithFlags(&S.ev_join, cudaEventDisableTiming);
    }
    for (int i = 0; i < 17; i++) S.key[i] = d_in[i];
    S.init = true;
  }
  if (!S.ok) return;

  cudaMemsetAsync(S.pM, 0xFF, sizeof(uint32_t) * 65 * 1792, st);
  cudaMemsetAsync(S.pS, 0, S.use_cluster ? sizeof(float4) * NSEG * NH * 5 * 32 : sizeof(g_S), st);
  cudaMemsetAsync(S.pF, 0, sizeof(uint32_t) * (NSEG + 64), st);

  ChainArgs ca;
  ca.mem0 = (const bf16*)d_in[10]; ca.Mg = (uint32_t*)S.pM; ca.Sg = (float4*)S.pS; ca.flag = (uint32_t*)S.pF; ca.dbg = (uint32_t*)S.pD;
  {
    cudaLaunchConfig_t cfg = {};
    cfg.gridDim = dim3(112); cfg.blockDim = dim3(CHAIN_THREADS); cfg.dynamicSmemBytes = SMEM_CHAIN; cfg.stream = st;
    cudaLaunchAttribute at[2];
    at[0].id = cudaLaunchAttributeLaunchCompletionEvent; at[0].val.launchCompletionEvent.event = S.ev_start; at[0].val.launchCompletionEvent.flags = 0;
    at[1].id = cudaLaunchAttributeClusterDimension; at[1].val.clusterDim.x = 16; at[1].val.clusterDim.y = 1; at[1].val.clusterDim.z = 1;
    cfg.attrs = at; cfg.numAttrs = S.use_cluster ? 2 : 1;
    if (S.use_cluster) cudaLaunchKernelEx(&cfg, chain_kernel<true>, S.tx, S.tq, S.tk, S.tv, S.to, S.tka, S.tya, ca);
    else cudaLaunchKernelEx(&cfg, chain_kernel<false>, S.tx, S.tq, S.tk, S.tv, S.to, S.tka, S.tya, ca);
  }
  cudaStreamWaitEvent(S.side, S.ev_start, 0);
  SsmArgs sa;
  sa.lam_re = (const bf16*)d_in[1]; sa.lam_im = (const bf16*)d_in[2]; sa.log_dt = (const bf16*)d_in[7]; sa.dskip = (const bf16*)d_in[8];
  sa.x = (const bf16*)d_in[0]; sa.gate_w = (const bf16*)d_in[16];
  sa.hloc = (float*)S.pH; sa.hend = (float2*)S.pE; sa.omg = (float*)S.pO; sa.out = (float*)d_out;
  ssm1_kernel<<<dim3(7, 16), 160, S1_SMEM, S.side>>>(S.tbre, S.tbim, S.txp, sa);
  ssm2_kernel<<<32, 288, S2_SMEM, S.side>>>(S.tcre, S.tcim, sa);
  AttnArgs aa;
  aa.flag = (const uint32_t*)S.pF; aa.ticket = (uint32_t*)S.pF + NSEG; aa.omg = (const float*)S.pO; aa.out = (float*)d_out;
  attn_kernel<<<S.n_free, 384, AT_SMEM, S.side>>>(S.tx64, S.tka, S.tya, aa);
  cudaEventRecord(S.ev_join, S.side);
  cudaStreamWaitEvent(st, S.ev_join, 0);
}
```

```cpp
#include <cuda_runtime.h>
#include <cuda_bf16.h>
#include <cuda.h>
#include <stdint.h>

typedef __nv_bfloat16 bf16;

namespace {

constexpr int NH = 16, DM = 448, DH = 256, SEQ = 2048, SEG = 32, NSEG = 64, NJ = 7, NMEM = 8, LKEY = 40;
constexpr int SPIN_LIMIT = 1 << 22;

#define KT_START(k) do {} while (0)
#define KT_END(k) do {} while (0)

__device__ __forceinline__ uint32_t smem_u32(const void* p) { return (uint32_t)__cvta_generic_to_shared(p); }
__device__ __forceinline__ void mbar_init(uint32_t a, uint32_t c) { asm volatile("mbarrier.init.shared.b64 [%0], %1;" ::"r"(a), "r"(c)); }
__device__ __forceinline__ void mbar_arrive(uint32_t a) { asm volatile("mbarrier.arrive.shared.b64 _, [%0];" ::"r"(a) : "memory"); }
__device__ __forceinline__ void mbar_expect_tx(uint32_t a, uint32_t b) { asm volatile("mbarrier.arrive.expect_tx.shared.b64 _, [%0], %1;" ::"r"(a), "r"(b) : "memory"); }
__device__ __forceinline__ bool mbar_try(uint32_t a, uint32_t parity) {
  uint32_t r;
  asm volatile("{\n.reg .pred p;\nmbarrier.try_wait.parity.shared.b64 p, [%1], %2;\nselp.u32 %0, 1, 0, p;\n}\n" : "=r"(r) : "r"(a), "r"(parity) : "memory");
  return r;
}
__device__ __forceinline__ bool mbar_try_cluster(uint32_t a, uint32_t parity) {
  uint32_t r;
  asm volatile("{\n.reg .pred p;\nmbarrier.try_wait.parity.acquire.cluster.shared.b64 p, [%1], %2;\nselp.u32 %0, 1, 0, p;\n}\n" : "=r"(r) : "r"(a), "r"(parity) : "memory");
  return r;
}
__device__ __forceinline__ bool mbar_test(uint32_t a, uint32_t parity) {
  uint32_t r;
  asm volatile("{\n.reg .pred p;\nmbarrier.test_wait.parity.shared.b64 p, [%1], %2;\nselp.u32 %0, 1, 0, p;\n}\n" : "=r"(r) : "r"(a), "r"(parity) : "memory");
  return r;
}
__device__ __forceinline__ void mbar_wait(uint32_t a, uint32_t parity) {
  int it = 0;
  while (!mbar_try(a, parity)) { if (++it > SPIN_LIMIT) break; }
}
__device__ __forceinline__ void mbar_wait_cluster(uint32_t a, uint32_t parity) {
  int it = 0;
  while (!mbar_try_cluster(a, parity)) { if (++it > SPIN_LIMIT) break; }
}
__device__ __forceinline__ uint32_t mapa(uint32_t a, uint32_t r) { uint32_t d; asm volatile("mapa.shared::cluster.u32 %0, %1, %2;" : "=r"(d) : "r"(a), "r"(r)); return d; }
__device__ __forceinline__ void cluster_sync_all() { asm volatile("barrier.cluster.arrive.aligned;\nbarrier.cluster.wait.aligned;" ::: "memory"); }
__device__ __forceinline__ void named_bar(int id, int n) { asm volatile("bar.sync %0, %1;" ::"r"(id), "r"(n) : "memory"); }
__device__ __forceinline__ void fence_async_smem() { asm volatile("fence.proxy.async.shared::cta;" ::: "memory"); }
__device__ __forceinline__ void fence_async_all() { asm volatile("fence.proxy.async;" ::: "memory"); }

__device__ __forceinline__ uint4 ld_vol_v4(const void* p) {
  uint4 v;
  asm volatile("ld.volatile.global.v4.u32 {%0,%1,%2,%3}, [%4];" : "=r"(v.x), "=r"(v.y), "=r"(v.z), "=r"(v.w) : "l"(p) : "memory");
  return v;
}
__device__ __forceinline__ uint32_t ld_acquire(const void* p) { uint32_t v; asm volatile("ld.acquire.gpu.global.u32 %0, [%1];" : "=r"(v) : "l"(p) : "memory"); return v; }
__device__ __forceinline__ void st_relaxed(void* p, uint32_t v) { asm volatile("st.relaxed.gpu.global.u32 [%0], %1;" ::"l"(p), "r"(v) : "memory"); }
__device__ __forceinline__ void red_v4(void* p, float a, float b, float c, float d) {
  asm volatile("red.relaxed.gpu.global.add.v4.f32 [%0], {%1,%2,%3,%4};" ::"l"(p), "f"(a), "f"(b), "f"(c), "f"(d) : "memory");
}
__device__ __forceinline__ void red_v2(void* p, float a, float b) {
  asm volatile("red.relaxed.gpu.global.add.v2.f32 [%0], {%1,%2};" ::"l"(p), "f"(a), "f"(b) : "memory");
}
__device__ __forceinline__ void red_u32(void* p, uint32_t v) { asm volatile("red.relaxed.gpu.global.add.u32 [%0], %1;" ::"l"(p), "r"(v) : "memory"); }
__device__ __forceinline__ void st_async_v4(uint32_t addr, float a, float b, float c, float d, uint32_t mbar) {
  asm volatile("st.async.shared::cluster.mbarrier::complete_tx::bytes.v4.f32 [%0], {%1,%2,%3,%4}, [%5];" ::"r"(addr), "f"(a), "f"(b), "f"(c), "f"(d), "r"(mbar) : "memory");
}

__device__ __forceinline__ void tma_load_2d(uint32_t dst, const CUtensorMap* tm, int c0, int c1, uint32_t mbar) {
  asm volatile("cp.async.bulk.tensor.2d.shared::cluster.global.mbarrier::complete_tx::bytes [%0], [%1, {%3, %4}], [%2];" ::"r"(dst), "l"(tm), "r"(mbar), "r"(c0), "r"(c1) : "memory");
}
__device__ __forceinline__ void tma_load_2d_mc(uint32_t dst, const CUtensorMap* tm, int c0, int c1, uint32_t mbar, uint16_t mask) {
  asm volatile("cp.async.bulk.tensor.2d.shared::cluster.global.mbarrier::complete_tx::bytes.multicast::cluster [%0], [%1, {%3, %4}], [%2], %5;" ::"r"(dst), "l"(tm), "r"(mbar), "r"(c0), "r"(c1), "h"(mask) : "memory");
}
__device__ __forceinline__ void tma_load_3d(uint32_t dst, const CUtensorMap* tm, int c0, int c1, int c2, uint32_t mbar) {
  asm volatile("cp.async.bulk.tensor.3d.shared::cluster.global.mbarrier::complete_tx::bytes [%0], [%1, {%3, %4, %5}], [%2];" ::"r"(dst), "l"(tm), "r"(mbar), "r"(c0), "r"(c1), "r"(c2) : "memory");
}
__device__ __forceinline__ void tma_load_4d(uint32_t dst, const CUtensorMap* tm, int c0, int c1, int c2, int c3, uint32_t mbar) {
  asm volatile("cp.async.bulk.tensor.4d.shared::cluster.global.mbarrier::complete_tx::bytes [%0], [%1, {%3, %4, %5, %6}], [%2];" ::"r"(dst), "l"(tm), "r"(mbar), "r"(c0), "r"(c1), "r"(c2), "r"(c3) : "memory");
}
__device__ __forceinline__ void tma_store_2d(const CUtensorMap* tm, int c0, int c1, uint32_t src) {
  asm volatile("cp.async.bulk.tensor.2d.global.shared::cta.bulk_group [%0, {%2, %3}], [%1];" ::"l"(tm), "r"(src), "r"(c0), "r"(c1) : "memory");
}
__device__ __forceinline__ void bulk_load(uint32_t dst, const void* src, uint32_t bytes, uint32_t mbar) {
  asm volatile("cp.async.bulk.shared::cluster.global.mbarrier::complete_tx::bytes [%0], [%1], %2, [%3];" ::"r"(dst), "l"(src), "r"(bytes), "r"(mbar) : "memory");
}
__device__ __forceinline__ void bulk_commit() { asm volatile("cp.async.bulk.commit_group;" ::: "memory"); }
template <int N> __device__ __forceinline__ void bulk_wait_read() { asm volatile("cp.async.bulk.wait_group.read %0;" ::"n"(N) : "memory"); }
template <int N> __device__ __forceinline__ void bulk_wait() { asm volatile("cp.async.bulk.wait_group %0;" ::"n"(N) : "memory"); }

__device__ __forceinline__ void wg_fence() { asm volatile("wgmma.fence.sync.aligned;" ::: "memory"); }
__device__ __forceinline__ void wg_commit() { asm volatile("wgmma.commit_group.sync.aligned;" ::: "memory"); }
template <int N> __device__ __forceinline__ void wg_wait() { asm volatile("wgmma.wait_group.sync.aligned %0;" ::"n"(N) : "memory"); }

__device__ __forceinline__ uint64_t desc_sw128(uint32_t addr) {
  return ((uint64_t)((addr & 0x3FFFF) >> 4)) | ((uint64_t)1 << 16) | ((uint64_t)(1024 >> 4) << 32) | ((uint64_t)1 << 62);
}

__device__ __forceinline__ uint32_t pack_bf16(float lo, float hi) {
  uint32_t r;
  asm("cvt.rn.bf16x2.f32 %0, %1, %2;" : "=r"(r) : "f"(hi), "f"(lo));
  return r;
}
__device__ __forceinline__ void mma16816(float* d, uint32_t a0, uint32_t a1, uint32_t a2, uint32_t a3, uint32_t b0, uint32_t b1) {
  asm volatile("mma.sync.aligned.m16n8k16.row.col.f32.bf16.bf16.f32 {%0,%1,%2,%3}, {%4,%5,%6,%7}, {%8,%9}, {%0,%1,%2,%3};"
               : "+f"(d[0]), "+f"(d[1]), "+f"(d[2]), "+f"(d[3]) : "r"(a0), "r"(a1), "r"(a2), "r"(a3), "r"(b0), "r"(b1));
}
__device__ __forceinline__ void mma1688(float* d, uint32_t a0, uint32_t a1, uint32_t b0) {
  asm volatile("mma.sync.aligned.m16n8k8.row.col.f32.bf16.bf16.f32 {%0,%1,%2,%3}, {%4,%5}, {%6}, {%0,%1,%2,%3};"
               : "+f"(d[0]), "+f"(d[1]), "+f"(d[2]), "+f"(d[3]) : "r"(a0), "r"(a1), "r"(b0));
}
__device__ __forceinline__ void ldsm_x4(uint32_t* r, uint32_t addr) {
  asm volatile("ldmatrix.sync.aligned.m8n8.x4.shared.b16 {%0,%1,%2,%3}, [%4];" : "=r"(r[0]), "=r"(r[1]), "=r"(r[2]), "=r"(r[3]) : "r"(addr) : "memory");
}
__device__ __forceinline__ void ldsm_x4_t(uint32_t* r, uint32_t addr) {
  asm volatile("ldmatrix.sync.aligned.m8n8.x4.trans.shared.b16 {%0,%1,%2,%3}, [%4];" : "=r"(r[0]), "=r"(r[1]), "=r"(r[2]), "=r"(r[3]) : "r"(addr) : "memory");
}
__device__ __forceinline__ void ldsm_x2_t(uint32_t* r, uint32_t addr) {
  asm volatile("ldmatrix.sync.aligned.m8n8.x2.trans.shared.b16 {%0,%1}, [%2];" : "=r"(r[0]), "=r"(r[1]) : "r"(addr) : "memory");
}
__device__ __forceinline__ void stsm_x4_t(uint32_t addr, uint32_t r0, uint32_t r1, uint32_t r2, uint32_t r3) {
  asm volatile("stmatrix.sync.aligned.m8n8.x4.trans.shared.b16 [%0], {%1,%2,%3,%4};" ::"r"(addr), "r"(r0), "r"(r1), "r"(r2), "r"(r3) : "memory");
}
__device__ __forceinline__ uint32_t movm_t(uint32_t a) { uint32_t d; asm volatile("movmatrix.sync.aligned.m8n8.trans.b16 %0, %1;" : "=r"(d) : "r"(a)); return d; }
__device__ __forceinline__ float ex2(float x) { float y; asm("ex2.approx.ftz.f32 %0, %1;" : "=f"(y) : "f"(x)); return y; }

__device__ __forceinline__ void wgmma_ss_n112(float* d, uint64_t descA, uint64_t descB, int scaleD) {
  asm volatile("{\n.reg .pred p;\nsetp.ne.b32 p, %58, 0;\n"
    "wgmma.mma_async.sync.aligned.m64n112k16.f32.bf16.bf16 {%0,%1,%2,%3,%4,%5,%6,%7,%8,%9,%10,%11,%12,%13,%14,%15,%16,%17,%18,%19,%20,%21,%22,%23,%24,%25,%26,%27,%28,%29,%30,%31,%32,%33,%34,%35,%36,%37,%38,%39,%40,%41,%42,%43,%44,%45,%46,%47,%48,%49,%50,%51,%52,%53,%54,%55}, %56, %57, p, 1, 1, 0, 0;\n}\n"
    : "+f"(d[0]),"+f"(d[1]),"+f"(d[2]),"+f"(d[3]),"+f"(d[4]),"+f"(d[5]),"+f"(d[6]),"+f"(d[7]),"+f"(d[8]),"+f"(d[9]),"+f"(d[10]),"+f"(d[11]),"+f"(d[12]),"+f"(d[13]),"+f"(d[14]),"+f"(d[15]),"+f"(d[16]),"+f"(d[17]),"+f"(d[18]),"+f"(d[19]),"+f"(d[20]),"+f"(d[21]),"+f"(d[22]),"+f"(d[23]),"+f"(d[24]),"+f"(d[25]),"+f"(d[26]),"+f"(d[27]),"+f"(d[28]),"+f"(d[29]),"+f"(d[30]),"+f"(d[31]),"+f"(d[32]),"+f"(d[33]),"+f"(d[34]),"+f"(d[35]),"+f"(d[36]),"+f"(d[37]),"+f"(d[38]),"+f"(d[39]),"+f"(d[40]),"+f"(d[41]),"+f"(d[42]),"+f"(d[43]),"+f"(d[44]),"+f"(d[45]),"+f"(d[46]),"+f"(d[47]),"+f"(d[48]),"+f"(d[49]),"+f"(d[50]),"+f"(d[51]),"+f"(d[52]),"+f"(d[53]),"+f"(d[54]),"+f"(d[55])
    : "l"(descA), "l"(descB), "r"(scaleD));
}
__device__ __forceinline__ void wgmma_ss_n112_ta(float* d, uint64_t descA, uint64_t descB, int scaleD) {
  asm volatile("{\n.reg .pred p;\nsetp.ne.b32 p, %58, 0;\n"
    "wgmma.mma_async.sync.aligned.m64n112k16.f32.bf16.bf16 {%0,%1,%2,%3,%4,%5,%6,%7,%8,%9,%10,%11,%12,%13,%14,%15,%16,%17,%18,%19,%20,%21,%22,%23,%24,%25,%26,%27,%28,%29,%30,%31,%32,%33,%34,%35,%36,%37,%38,%39,%40,%41,%42,%43,%44,%45,%46,%47,%48,%49,%50,%51,%52,%53,%54,%55}, %56, %57, p, 1, 1, 1, 0;\n}\n"
    : "+f"(d[0]),"+f"(d[1]),"+f"(d[2]),"+f"(d[3]),"+f"(d[4]),"+f"(d[5]),"+f"(d[6]),"+f"(d[7]),"+f"(d[8]),"+f"(d[9]),"+f"(d[10]),"+f"(d[11]),"+f"(d[12]),"+f"(d[13]),"+f"(d[14]),"+f"(d[15]),"+f"(d[16]),"+f"(d[17]),"+f"(d[18]),"+f"(d[19]),"+f"(d[20]),"+f"(d[21]),"+f"(d[22]),"+f"(d[23]),"+f"(d[24]),"+f"(d[25]),"+f"(d[26]),"+f"(d[27]),"+f"(d[28]),"+f"(d[29]),"+f"(d[30]),"+f"(d[31]),"+f"(d[32]),"+f"(d[33]),"+f"(d[34]),"+f"(d[35]),"+f"(d[36]),"+f"(d[37]),"+f"(d[38]),"+f"(d[39]),"+f"(d[40]),"+f"(d[41]),"+f"(d[42]),"+f"(d[43]),"+f"(d[44]),"+f"(d[45]),"+f"(d[46]),"+f"(d[47]),"+f"(d[48]),"+f"(d[49]),"+f"(d[50]),"+f"(d[51]),"+f"(d[52]),"+f"(d[53]),"+f"(d[54]),"+f"(d[55])
    : "l"(descA), "l"(descB), "r"(scaleD));
}
__device__ __forceinline__ void wgmma_rs_n32(float* d, const uint32_t* a, uint64_t descB, int scaleD) {
  asm volatile("{\n.reg .pred p;\nsetp.ne.b32 p, %21, 0;\n"
    "wgmma.mma_async.sync.aligned.m64n32k16.f32.bf16.bf16 {%0,%1,%2,%3,%4,%5,%6,%7,%8,%9,%10,%11,%12,%13,%14,%15}, {%16,%17,%18,%19}, %20, p, 1, 1, 0;\n}\n"
    : "+f"(d[0]),"+f"(d[1]),"+f"(d[2]),"+f"(d[3]),"+f"(d[4]),"+f"(d[5]),"+f"(d[6]),"+f"(d[7]),"+f"(d[8]),"+f"(d[9]),"+f"(d[10]),"+f"(d[11]),"+f"(d[12]),"+f"(d[13]),"+f"(d[14]),"+f"(d[15])
    : "r"(a[0]), "r"(a[1]), "r"(a[2]), "r"(a[3]), "l"(descB), "r"(scaleD));
}
__device__ __forceinline__ void wgmma_ss_n128(float* d, uint64_t descA, uint64_t descB, int scaleD) {
  asm volatile("{\n.reg .pred p;\nsetp.ne.b32 p, %66, 0;\n"
    "wgmma.mma_async.sync.aligned.m64n128k16.f32.bf16.bf16 {%0,%1,%2,%3,%4,%5,%6,%7,%8,%9,%10,%11,%12,%13,%14,%15,%16,%17,%18,%19,%20,%21,%22,%23,%24,%25,%26,%27,%28,%29,%30,%31,%32,%33,%34,%35,%36,%37,%38,%39,%40,%41,%42,%43,%44,%45,%46,%47,%48,%49,%50,%51,%52,%53,%54,%55,%56,%57,%58,%59,%60,%61,%62,%63}, %64, %65, p, 1, 1, 0, 0;\n}\n"
    : "+f"(d[0]),"+f"(d[1]),"+f"(d[2]),"+f"(d[3]),"+f"(d[4]),"+f"(d[5]),"+f"(d[6]),"+f"(d[7]),"+f"(d[8]),"+f"(d[9]),"+f"(d[10]),"+f"(d[11]),"+f"(d[12]),"+f"(d[13]),"+f"(d[14]),"+f"(d[15]),"+f"(d[16]),"+f"(d[17]),"+f"(d[18]),"+f"(d[19]),"+f"(d[20]),"+f"(d[21]),"+f"(d[22]),"+f"(d[23]),"+f"(d[24]),"+f"(d[25]),"+f"(d[26]),"+f"(d[27]),"+f"(d[28]),"+f"(d[29]),"+f"(d[30]),"+f"(d[31]),"+f"(d[32]),"+f"(d[33]),"+f"(d[34]),"+f"(d[35]),"+f"(d[36]),"+f"(d[37]),"+f"(d[38]),"+f"(d[39]),"+f"(d[40]),"+f"(d[41]),"+f"(d[42]),"+f"(d[43]),"+f"(d[44]),"+f"(d[45]),"+f"(d[46]),"+f"(d[47]),"+f"(d[48]),"+f"(d[49]),"+f"(d[50]),"+f"(d[51]),"+f"(d[52]),"+f"(d[53]),"+f"(d[54]),"+f"(d[55]),"+f"(d[56]),"+f"(d[57]),"+f"(d[58]),"+f"(d[59]),"+f"(d[60]),"+f"(d[61]),"+f"(d[62]),"+f"(d[63])
    : "l"(descA), "l"(descB), "r"(scaleD));
}
__device__ __forceinline__ void wgmma_ss_n40(float* d, uint64_t descA, uint64_t descB, int scaleD) {
  asm volatile("{\n.reg .pred p;\nsetp.ne.b32 p, %22, 0;\n"
    "wgmma.mma_async.sync.aligned.m64n40k16.f32.bf16.bf16 {%0,%1,%2,%3,%4,%5,%6,%7,%8,%9,%10,%11,%12,%13,%14,%15,%16,%17,%18,%19}, %20, %21, p, 1, 1, 0, 0;\n}\n"
    : "+f"(d[0]),"+f"(d[1]),"+f"(d[2]),"+f"(d[3]),"+f"(d[4]),"+f"(d[5]),"+f"(d[6]),"+f"(d[7]),"+f"(d[8]),"+f"(d[9]),"+f"(d[10]),"+f"(d[11]),"+f"(d[12]),"+f"(d[13]),"+f"(d[14]),"+f"(d[15]),"+f"(d[16]),"+f"(d[17]),"+f"(d[18]),"+f"(d[19])
    : "l"(descA), "l"(descB), "r"(scaleD));
}
__device__ __forceinline__ void wgmma_rs_n64_tb(float* d, const uint32_t* a, uint64_t descB, int scaleD) {
  asm volatile("{\n.reg .pred p;\nsetp.ne.b32 p, %37, 0;\n"
    "wgmma.mma_async.sync.aligned.m64n64k16.f32.bf16.bf16 {%0,%1,%2,%3,%4,%5,%6,%7,%8,%9,%10,%11,%12,%13,%14,%15,%16,%17,%18,%19,%20,%21,%22,%23,%24,%25,%26,%27,%28,%29,%30,%31}, {%32,%33,%34,%35}, %36, p, 1, 1, 1;\n}\n"
    : "+f"(d[0]),"+f"(d[1]),"+f"(d[2]),"+f"(d[3]),"+f"(d[4]),"+f"(d[5]),"+f"(d[6]),"+f"(d[7]),"+f"(d[8]),"+f"(d[9]),"+f"(d[10]),"+f"(d[11]),"+f"(d[12]),"+f"(d[13]),"+f"(d[14]),"+f"(d[15]),"+f"(d[16]),"+f"(d[17]),"+f"(d[18]),"+f"(d[19]),"+f"(d[20]),"+f"(d[21]),"+f"(d[22]),"+f"(d[23]),"+f"(d[24]),"+f"(d[25]),"+f"(d[26]),"+f"(d[27]),"+f"(d[28]),"+f"(d[29]),"+f"(d[30]),"+f"(d[31])
    : "r"(a[0]), "r"(a[1]), "r"(a[2]), "r"(a[3]), "l"(descB), "r"(scaleD));
}
struct ChainArgs {
  const bf16* mem0;
  uint32_t* Mg;
  float4* Sg;
  uint32_t* flag;
  uint32_t* dbg;
};

constexpr int XT_BYTES = 28672;
constexpr int STG_BYTES = 5120;
constexpr int OFF_A = 0, OFF_B = 65536, OFF_C = OFF_B + 3 * XT_BYTES, OFF_M = OFF_C + 2 * XT_BYTES, OFF_P = OFF_M + 2 * 7168,
              OFF_SX = OFF_P + 4096, OFF_SM = OFF_SX + 2048, OFF_SW = OFF_SM + 512, OFF_BAR = OFF_SW + 1024, OFF_DBG = OFF_B + 2 * XT_BYTES + 3 * 7168, SMEM_CHAIN = OFF_BAR + 512;
enum { B_PA = 0, B_PE = 1, B_XF = 4, B_MB = 9, B_SX = 11, B_SM = 13, B_PB = 15, B_KR = 17, B_ST = 21, B_PF = 29, B_RD = 45, B_MF = 47, B_EM = 51, B_SB = 55, B_PE5 = 56, B_NUM = 61 };
#define MD0 250
#define MDELTA 900
#define SSTART 850
#define SXSTART 700
#define SSTAG 130
constexpr float L2E = 1.4426950408889634f;
constexpr int CHAIN_THREADS = 512;
#define TOKK 28

__device__ __forceinline__ uint32_t xstage_off(int st) { return st < 2 ? OFF_C + st * XT_BYTES : OFF_B + (st - 2) * XT_BYTES; }
__device__ __forceinline__ uint32_t mslot_off(int k) { return k < 3 ? OFF_B + 2 * XT_BYTES + k * 7168 : OFF_M; }
constexpr int OFF_VAR = OFF_BAR + 496;

__device__ __forceinline__ bool slot_has_sentinel(const uint8_t* p, int lane) {
  bool bad = false;
#pragma unroll 2
  for (int i = 0; i < 14; i++) { const uint4 v = *reinterpret_cast<const uint4*>(p + (32 * i + lane) * 16); bad |= (v.x == ~0u) | (v.y == ~0u) | (v.z == ~0u) | (v.w == ~0u); }
  return __any_sync(~0u, bad);
}
__device__ __forceinline__ uint32_t clk32() { uint32_t c; asm volatile("mov.u32 %0, %%clock;" : "=r"(c)); return c; }
#define DBG(slot) do {} while (0)

template <bool CL>
__device__ __forceinline__ void issue_x_load(uint32_t sb, const CUtensorMap* tm_x, const CUtensorMap* tm_x3, int seg, int rank) {
  const int st = seg & 3;
  const uint32_t bar = sb + OFF_BAR + (B_XF + st) * 8;
  const uint32_t dst = sb + xstage_off(st);
  mbar_expect_tx(bar, XT_BYTES);
  if (CL) {
    if (rank < NJ) tma_load_2d_mc(dst + rank * 4096, tm_x, rank * 64, seg * SEG, bar, (uint16_t)0xFFFF);
  } else {
    tma_load_3d(dst, tm_x3, 0, seg * SEG, 0, bar);
  }
}

template <int WG>
__device__ __forceinline__ void tile_prologue(uint32_t* W, uint32_t sb) {
  const uint32_t bar = sb + OFF_BAR;
  const int lane = threadIdx.x & 31;
  float acc[112];
  mbar_wait(bar + B_PA * 8, 0);
#pragma unroll
  for (int half = 0; half < 2; half++) {
#pragma unroll
    for (int ec = 0; ec < 4; ec++) {
      const int i = half * 8 + ec * 2 + WG;
      const int st = i % 5;
      mbar_wait(bar + (B_PF + i) * 8, 0);
      const uint32_t bb = sb + OFF_B + st * XT_BYTES;
      wg_fence();
#pragma unroll
      for (int kk = 0; kk < 4; kk++) {
        if (WG == 0) {
          wgmma_ss_n112(acc, desc_sw128(sb + OFF_A + ec * 8192 + kk * 32), desc_sw128(bb + kk * 32), (ec | kk) != 0);
          wgmma_ss_n112(acc + 56, desc_sw128(sb + OFF_A + ec * 8192 + kk * 32), desc_sw128(bb + 14336 + kk * 32), (ec | kk) != 0);
        } else {
          wgmma_ss_n112_ta(acc, desc_sw128(sb + OFF_A + 32768 + (ec * 64 + kk * 16) * 128), desc_sw128(bb + kk * 32), (ec | kk) != 0);
          wgmma_ss_n112_ta(acc + 56, desc_sw128(sb + OFF_A + 32768 + (ec * 64 + kk * 16) * 128), desc_sw128(bb + 14336 + kk * 32), (ec | kk) != 0);
        }
      }
      wg_commit();
      wg_wait<0>();
      if (lane == 0) mbar_arrive(bar + (B_PE5 + st) * 8);
    }
    const float sc = WG == 0 ? 0.0625f : 1.0f;
#pragma unroll
    for (int kk = 0; kk < 14; kk++) {
      W[half * 56 + kk * 4 + 0] = pack_bf16(acc[8 * kk + 0] * sc, acc[8 * kk + 1] * sc);
      W[half * 56 + kk * 4 + 1] = pack_bf16(acc[8 * kk + 2] * sc, acc[8 * kk + 3] * sc);
      W[half * 56 + kk * 4 + 2] = pack_bf16(acc[8 * kk + 4] * sc, acc[8 * kk + 5] * sc);
      W[half * 56 + kk * 4 + 3] = pack_bf16(acc[8 * kk + 6] * sc, acc[8 * kk + 7] * sc);
    }
  }
}

__device__ __forceinline__ void token_gemm(const uint32_t* W, uint32_t sb, int seg, uint32_t stg_base, int w, int lane) {
  const int st = seg & 3;
  mbar_wait(sb + OFF_BAR + (B_XF + st) * 8, (seg >> 2) & 1);
  const uint32_t xb = sb + xstage_off(st);
  float d[16];
  wg_fence();
#pragma unroll
  for (int kk = 0; kk < TOKK; kk++) wgmma_rs_n32(d, &W[4 * kk], desc_sw128(xb + (kk >> 2) * 4096 + (kk & 3) * 32), kk != 0);
  wg_commit();
  wg_wait<0>();
  const uint32_t stg = stg_base + (seg & 3) * STG_BYTES + 1024;
  const int r = lane & 7, mi = lane >> 3;
#pragma unroll
  for (int p = 0; p < 2; p++) {
    const int t = 8 * (2 * p + (mi >> 1)) + r;
    const int chunk = 2 * w + (mi & 1);
    const uint32_t addr = stg + t * 128 + ((chunk ^ r) << 4);
    stsm_x4_t(addr, pack_bf16(d[8 * p + 0], d[8 * p + 1]), pack_bf16(d[8 * p + 2], d[8 * p + 3]), pack_bf16(d[8 * p + 4], d[8 * p + 5]),
              pack_bf16(d[8 * p + 6], d[8 * p + 7]));
  }
}

__device__ __forceinline__ void poll_smm(uint8_t* smem, uint32_t bar, const float4* src, int s, int p, int lane) {
  volatile uint32_t* var = reinterpret_cast<volatile uint32_t*>(smem + OFF_VAR);
  { int it = 0; while (var[1] != (uint32_t)s && ++it < SPIN_LIMIT) __nanosleep(20); }
  const uint32_t tM = clk32();
  while ((int)(clk32() - tM) < SSTART + p * SSTAG) {}
  uint4 v; int it = 0; bool mine = true;
  while (true) {
    v = ld_vol_v4(src);
    if (__all_sync(~0u, __uint_as_float(v.z) == 7.f)) break;
    if (mbar_test(bar + (B_SM + (s & 1)) * 8, (s >> 1) & 1)) { mine = false; break; }
    if (++it > SPIN_LIMIT) break;
  }
  if (mine) {
    reinterpret_cast<float2*>(smem + OFF_SM + (s & 1) * 256)[lane] = make_float2(__uint_as_float(v.x), __uint_as_float(v.y));
    __syncwarp();
    if (lane == 0) { if (atomicExch(reinterpret_cast<uint32_t*>(smem + OFF_VAR), (uint32_t)(s + 1)) != (uint32_t)(s + 1)) mbar_arrive(bar + (B_SM + (s & 1)) * 8); }
  }
}

template <bool CL>
__global__ void __launch_bounds__(CHAIN_THREADS, 1)
chain_kernel(const __grid_constant__ CUtensorMap tm_x, const __grid_constant__ CUtensorMap tm_wq, const __grid_constant__ CUtensorMap tm_wk,
             const __grid_constant__ CUtensorMap tm_wv, const __grid_constant__ CUtensorMap tm_wo, const __grid_constant__ CUtensorMap tm_k,
             const __grid_constant__ CUtensorMap tm_y, const __grid_constant__ CUtensorMap tm_x3, ChainArgs args) {
  extern __shared__ __align__(1024) uint8_t smem[];
  const uint32_t sb = smem_u32(smem);
  const int tid = threadIdx.x, warp = tid >> 5, lane = tid & 31;
  const int j = blockIdx.x >> 4, h = blockIdx.x & 15;
  const uint32_t bar = sb + OFF_BAR;
  const int g = lane >> 2, q = lane & 3;
  KT_START(0);

  if (tid == 0) {
    mbar_init(bar + B_PA * 8, 1);
    for (int i = 0; i < 5; i++) mbar_init(bar + (B_PE5 + i) * 8, 4);
    for (int i = 0; i < 16; i++) mbar_init(bar + (B_PF + i) * 8, 1);
    for (int i = 0; i < 5; i++) mbar_init(bar + (B_XF + i) * 8, 1);
    for (int i = 0; i < 2; i++) {
      mbar_init(bar + (B_SX + i) * 8, 4); mbar_init(bar + (B_SM + i) * 8, 1); mbar_init(bar + (B_PB + i) * 8, 1); mbar_init(bar + (B_RD + i) * 8, 1);
    }
    for (int i = 0; i < 4; i++) { mbar_init(bar + (B_KR + i) * 8, 4); mbar_init(bar + (B_MF + i) * 8, 1); mbar_init(bar + (B_EM + i) * 8, 4); }
    mbar_init(bar + B_SB * 8, 1);
    for (int i = 0; i < 8; i++) mbar_init(bar + (B_ST + i) * 8, 4);
    asm volatile("fence.mbarrier_init.release.cluster;" ::: "memory");
  }
  __syncthreads();
  if (CL) cluster_sync_all();
  asm volatile("griddepcontrol.launch_dependents;" ::: "memory");

  const int wgi = __shfl_sync(0xffffffffu, tid >> 7, 0);
  if (wgi < 2) {
    asm volatile("setmaxnreg.inc.sync.aligned.u32 200;");
    const int wg = wgi, w = warp & 3;
    uint32_t W[112];
    if (wg == 0) tile_prologue<0>(W, sb); else tile_prologue<1>(W, sb);
    named_bar(0, CHAIN_THREADS);
    if (CL) cluster_sync_all();

    const uint32_t stg_base = sb + OFF_A + wg * 4 * STG_BYTES;
    token_gemm(W, sb, 0, stg_base, w, lane);
    token_gemm(W, sb, 1, stg_base, w, lane);
    __syncwarp();
    if (wg == 0 && lane == 0) { mbar_arrive(bar + (B_KR + 0) * 8); mbar_arrive(bar + (B_KR + 1) * 8); }

    if (wg == 0) {
      for (int s = 0; s < NSEG; s++) {
        float d0, d1, d2, d3;
        uint32_t ma[2];
        volatile uint32_t* var = reinterpret_cast<volatile uint32_t*>(smem + OFF_VAR);
        mbar_wait(bar + B_SB * 8, s & 1);
        uint32_t n = var[3];
        const uint32_t n_first = n;
        while (true) {
          const int slot = n & 3;
          mbar_wait(bar + (B_MF + slot) * 8, (n >> 2) & 1);
          if (tid == 0) DBG(0);
          const uint32_t ms = sb + mslot_off(slot);
          float a4[4][4];
#pragma unroll
          for (int i = 0; i < 4; i++) { a4[i][0] = a4[i][1] = a4[i][2] = a4[i][3] = 0.f; }
          uint32_t b[14][4];
#pragma unroll
          for (int i = 0; i < 14; i++) ldsm_x4_t(b[i], ms + (32 * i + lane) * 16);
          ldsm_x2_t(ma, ms + (64 * j + 16 * w + (lane & 15)) * 16);
#pragma unroll
          for (int i = 0; i < 14; i++) {
            mma16816(a4[(2 * i) & 3], W[8 * i + 0], W[8 * i + 1], W[8 * i + 2], W[8 * i + 3], b[i][0], b[i][1]);
            mma16816(a4[(2 * i + 1) & 3], W[8 * i + 4], W[8 * i + 5], W[8 * i + 6], W[8 * i + 7], b[i][2], b[i][3]);
          }
          d0 = (a4[0][0] + a4[1][0]) + (a4[2][0] + a4[3][0]); d1 = (a4[0][1] + a4[1][1]) + (a4[2][1] + a4[3][1]);
          d2 = (a4[0][2] + a4[1][2]) + (a4[2][2] + a4[3][2]); d3 = (a4[0][3] + a4[1][3]) + (a4[2][3] + a4[3][3]);
          if (!__any_sync(~0u, (d0 != d0) | (d1 != d1))) break;
          if (!slot_has_sentinel(smem + mslot_off(slot), lane)) break;
          if (n - n_first > (uint32_t)SPIN_LIMIT) break;
          if (lane == 0) mbar_arrive(bar + (B_EM + slot) * 8);
          n++;
        }
        if (tid == 0) { var[2] = n; var[1] = s; reinterpret_cast<uint32_t*>(smem + OFF_DBG)[s * 16 + 14] = n - n_first; }
        asm volatile("bar.arrive 5, 256;" ::: "memory");
        if (tid == 0) { asm volatile("" :: "f"(d0), "f"(d3)); DBG(8); }
        const uint32_t kb0 = movm_t(pack_bf16(d0, d1)), kb1 = movm_t(pack_bf16(d2, d3));
        if (s < NSEG - 1) {
          float c[4] = {0.f, 0.f, 0.f, 0.f};
          mma16816(c, ma[0], 0u, ma[1], 0u, kb0, kb1);
          float2* sw = reinterpret_cast<float2*>(smem + OFF_SW);
          sw[w * 32 + lane] = make_float2(c[0], c[1]);
          if (tid == 0) DBG(9);
          named_bar(1, 128);
          if (tid == 0) DBG(10);
          if (w == 0) {
            const float2 v0 = sw[lane], v1 = sw[32 + lane], v2 = sw[64 + lane], v3 = sw[96 + lane];
            red_v4(args.Sg + (((size_t)s * NH + h) * 5 + 4) * 32 + lane, (v0.x + v1.x) + (v2.x + v3.x), (v0.y + v1.y) + (v2.y + v3.y), 1.f, 0.f);
          }
        }
        asm volatile("bar.arrive 3, 256;" ::: "memory");
        if (tid == 0) DBG(1);
        {
          const uint32_t stg = stg_base + (s & 3) * STG_BYTES + g * 128 + q * 4;
          asm volatile("st.shared.u32 [%0], %1;" ::"r"(stg + (((2 * w) ^ g) << 4)), "r"(kb0) : "memory");
          asm volatile("st.shared.u32 [%0], %1;" ::"r"(stg + (((2 * w + 1) ^ g) << 4)), "r"(kb1) : "memory");
          fence_async_smem();
          __syncwarp();
          if (lane == 0) mbar_arrive(bar + (B_ST + (s & 3)) * 8);
        }
        if (s + 2 < NSEG) {
          token_gemm(W, sb, s + 2, stg_base, w, lane);
          __syncwarp();
          if (lane == 0) mbar_arrive(bar + (B_KR + ((s + 2) & 3)) * 8);
        }
        if (tid == 0) DBG(11);
        named_bar(1, 128);
      }
    } else {
      const int hd = w * 4 + (lane >> 3);
      uint32_t p_dst = sb + OFF_P + h * 128 + (lane & 7) * 16, p_bar = bar + B_PB * 8;
      if (CL) { p_dst = mapa(p_dst, hd); p_bar = mapa(p_bar, hd); }
      const uint32_t ONE2 = 0x3F803F80u;
      for (int s = 0; s < NSEG; s++) {
        if (s < NSEG - 1) {
          mbar_wait(bar + (B_KR + (s & 3)) * 8, (s >> 2) & 1);
          const uint32_t kst = sb + OFF_A + (s & 3) * STG_BYTES + 1024;
          uint32_t bk[2][4];
#pragma unroll
          for (int i = 0; i < 2; i++) ldsm_x4(bk[i], kst + (8 * w + (lane & 7)) * 128 + (((4 * i + (lane >> 3)) ^ (lane & 7)) << 4));
          float c[4] = {0.f, 0.f, 0.f, 0.f}, c2[4] = {0.f, 0.f, 0.f, 0.f};
          named_bar(5, 256);
          {
            const uint32_t ms = sb + mslot_off(reinterpret_cast<volatile uint32_t*>(smem + OFF_VAR)[2] & 3);
            uint32_t a[2][4];
            ldsm_x4_t(a[0], ms + (64 * j + lane) * 16);
            ldsm_x4_t(a[1], ms + (64 * j + 32 + lane) * 16);
            mma16816(c, a[0][0], 0u, a[0][1], 0u, bk[0][0], bk[0][1]);
            mma16816(c2, a[0][2], 0u, a[0][3], 0u, bk[0][2], bk[0][3]);
            mma16816(c, a[1][0], 0u, a[1][1], 0u, bk[1][0], bk[1][1]);
            mma16816(c2, a[1][2], 0u, a[1][3], 0u, bk[1][2], bk[1][3]);
            c[0] += c2[0]; c[1] += c2[1];
          }
          red_v4(args.Sg + (((size_t)s * NH + h) * 5 + w) * 32 + lane, c[0], c[1], 1.f, 0.f);
        } else named_bar(5, 256);
        named_bar(3, 256);
        const uint32_t ms = sb + mslot_off(reinterpret_cast<volatile uint32_t*>(smem + OFF_VAR)[2] & 3);
        float a4[4][4];
#pragma unroll
        for (int i = 0; i < 4; i++) { a4[i][0] = a4[i][1] = a4[i][2] = a4[i][3] = 0.f; }
        {
          uint32_t b[14][4];
#pragma unroll
          for (int i = 0; i < 14; i++) ldsm_x4_t(b[i], ms + (32 * i + lane) * 16);
#pragma unroll
          for (int i = 0; i < 14; i++) {
            mma16816(a4[(2 * i) & 3], W[8 * i + 0], W[8 * i + 1], W[8 * i + 2], W[8 * i + 3], b[i][0], b[i][1]);
            mma16816(a4[(2 * i + 1) & 3], W[8 * i + 4], W[8 * i + 5], W[8 * i + 6], W[8 * i + 7], b[i][2], b[i][3]);
          }
        }
        const uint32_t za0 = pack_bf16((a4[0][0] + a4[1][0]) + (a4[2][0] + a4[3][0]), (a4[0][1] + a4[1][1]) + (a4[2][1] + a4[3][1]));
        const uint32_t za1 = pack_bf16((a4[0][2] + a4[1][2]) + (a4[2][2] + a4[3][2]), (a4[0][3] + a4[1][3]) + (a4[2][3] + a4[3][3]));
        {
          const uint32_t stg = stg_base + (s & 3) * STG_BYTES + g * 128 + q * 4;
          asm volatile("st.shared.u32 [%0], %1;" ::"r"(stg + (((2 * w) ^ g) << 4)), "r"(movm_t(za0)) : "memory");
          asm volatile("st.shared.u32 [%0], %1;" ::"r"(stg + (((2 * w + 1) ^ g) << 4)), "r"(movm_t(za1)) : "memory");
          fence_async_smem();
          __syncwarp();
          if (lane == 0) mbar_arrive(bar + (B_ST + 4 + (s & 3)) * 8);
        }
        if (s < NSEG - 1) {
          uint32_t va[2][4];
          const uint32_t vst = stg_base + (s & 3) * STG_BYTES + 1024;
#pragma unroll
          for (int kk = 0; kk < 2; kk++) {
            const int mi = lane >> 3, r = lane & 7;
            const int t = 8 * (2 * kk + (mi >> 1)) + r;
            ldsm_x4_t(va[kk], vst + t * 128 + (((2 * w + (mi & 1)) ^ r) << 4));
          }
          mbar_wait(bar + (B_SX + (s & 1)) * 8, (s >> 1) & 1);
          const float2* sx = reinterpret_cast<const float2*>(smem + OFF_SX + (s & 1) * 1024);
          float ex[8];
#pragma unroll
          for (int nt = 0; nt < 4; nt++) { const float2 v = sx[nt * 32 + lane]; ex[2 * nt] = v.x; ex[2 * nt + 1] = v.y; }
          float mx = fmaxf(fmaxf(fmaxf(ex[0], ex[1]), fmaxf(ex[2], ex[3])), fmaxf(fmaxf(ex[4], ex[5]), fmaxf(ex[6], ex[7])));
          mx = fmaxf(mx, __shfl_xor_sync(~0u, mx, 1));
          mx = fmaxf(mx, __shfl_xor_sync(~0u, mx, 2));
#pragma unroll
          for (int k = 0; k < 8; k++) ex[k] = ex2((ex[k] - mx) * L2E);
          mbar_wait(bar + (B_SM + (s & 1)) * 8, (s >> 1) & 1);
          if (tid == 128) DBG(2);
          const float2 sm = reinterpret_cast<const float2*>(smem + OFF_SM + (s & 1) * 256)[lane];
          float mm = fmaxf(sm.x, sm.y);
          mm = fmaxf(mm, __shfl_xor_sync(~0u, mm, 1));
          mm = fmaxf(mm, __shfl_xor_sync(~0u, mm, 2));
          const float m = fmaxf(mx, mm);
          const float f = ex2((mx - m) * L2E);
          const uint32_t pm = pack_bf16(ex2((sm.x - m) * L2E), ex2((sm.y - m) * L2E));
          uint32_t bx[4];
#pragma unroll
          for (int nt = 0; nt < 4; nt++) bx[nt] = pack_bf16(ex[2 * nt] * f, ex[2 * nt + 1] * f);
          float o0[4] = {0.f, 0.f, 0.f, 0.f}, o1[4] = {0.f, 0.f, 0.f, 0.f}, o2[4] = {0.f, 0.f, 0.f, 0.f};
          float l0[4] = {0.f, 0.f, 0.f, 0.f}, l1[4] = {0.f, 0.f, 0.f, 0.f}, l2[4] = {0.f, 0.f, 0.f, 0.f};
          mma1688(o0, za0, za1, pm);
          mma1688(l0, ONE2, ONE2, pm);
          mma16816(o1, va[0][0], va[0][1], va[0][2], va[0][3], bx[0], bx[1]);
          mma16816(l1, ONE2, ONE2, ONE2, ONE2, bx[0], bx[1]);
          mma16816(o2, va[1][0], va[1][1], va[1][2], va[1][3], bx[2], bx[3]);
          mma16816(l2, ONE2, ONE2, ONE2, ONE2, bx[2], bx[3]);
          const float r0 = __fdividef(1.f, l0[0] + l1[0] + l2[0]), r1 = __fdividef(1.f, l0[1] + l1[1] + l2[1]);
          const float v0 = (o0[0] + o1[0] + o2[0]) * r0, v1 = (o0[1] + o1[1] + o2[1]) * r1;
          const float v2 = (o0[2] + o1[2] + o2[2]) * r0, v3 = (o0[3] + o1[3] + o2[3]) * r1;
          if (CL) {
            st_async_v4(p_dst + (s & 1) * 2048, v0, v1, v2, v3, p_bar + (s & 1) * 8);
          } else {
            uint4* dst = reinterpret_cast<uint4*>(args.Sg + (size_t)NSEG * NH * 5 * 32) + ((((size_t)s * NJ + j) * 16 + hd) * 16 + h) * 8 + (lane & 7);
            uint32_t u0 = ~__float_as_uint(v0), u1 = ~__float_as_uint(v1), u2 = ~__float_as_uint(v2), u3 = ~__float_as_uint(v3);
            u0 += (u0 == 0); u1 += (u1 == 0); u2 += (u2 == 0); u3 += (u3 == 0);
            asm volatile("st.relaxed.gpu.global.v4.u32 [%0], {%1,%2,%3,%4};" ::"l"(dst), "r"(u0), "r"(u1), "r"(u2), "r"(u3) : "memory");
          }
          if (tid == 128) DBG(3);
        }
        if (s + 2 < NSEG) token_gemm(W, sb, s + 2, stg_base, w, lane);
        if (tid == 128) DBG(12);
      }
    }
  } else if (wgi == 2) {
    asm volatile("setmaxnreg.dec.sync.aligned.u32 80;");
    const int aw = warp - 8, at = tid - 256;
    named_bar(0, CHAIN_THREADS);
    if (CL) cluster_sync_all();
    for (int s = 0; s < NSEG; s++) {
      volatile uint32_t* var = reinterpret_cast<volatile uint32_t*>(smem + OFF_VAR);
      if (s == 0) {
        for (int c = at; c < DM; c += 128) {
          uint32_t v[4];
#pragma unroll
          for (int i = 0; i < 4; i++) {
            uint32_t lo = reinterpret_cast<const uint16_t*>(args.mem0)[(2 * i) * DM + c], hi = reinterpret_cast<const uint16_t*>(args.mem0)[(2 * i + 1) * DM + c];
            if (lo == 0xFFFFu) lo = 0x7FFFu;
            if (hi == 0xFFFFu) hi = 0x7FFFu;
            v[i] = lo | (hi << 16);
          }
          *reinterpret_cast<uint4*>(smem + mslot_off(0) + c * 16) = make_uint4(v[0], v[1], v[2], v[3]);
        }
        named_bar(2, 128);
        if (at == 0) mbar_arrive(bar + B_MF * 8);
      }
      { int it = 0; while (var[1] != (uint32_t)s && ++it < SPIN_LIMIT) __nanosleep(20); }
      if (j == 0) {
        const float4 z4 = make_float4(0.f, 0.f, 0.f, 0.f);
        if (s >= 2) { float4* p = args.Sg + ((size_t)(s - 2) * NH + h) * 160; p[aw * 32 + lane] = z4; if (aw == 0) p[128 + lane] = z4; }
        if (s == NSEG - 1) { float4* p = args.Sg + ((size_t)(s - 1) * NH + h) * 160; p[aw * 32 + lane] = z4; if (aw == 0) p[128 + lane] = z4; }
      }
      if (at == 32) DBG(4);
      if (s == NSEG - 1) break;
      const uint32_t tM = clk32();
      {
        const float4* src = args.Sg + (((size_t)s * NH + h) * 5 + aw) * 32 + lane;
        while ((int)(clk32() - tM) < SXSTART) {}
        uint4 v; int it = 0;
        do { v = ld_vol_v4(src); } while (__uint_as_float(v.z) != 7.f && ++it < SPIN_LIMIT);
        reinterpret_cast<float2*>(smem + OFF_SX + (s & 1) * 1024)[aw * 32 + lane] = make_float2(__uint_as_float(v.x), __uint_as_float(v.y));
        __syncwarp();
        if (lane == 0) mbar_arrive(bar + (B_SX + (s & 1)) * 8);
        if (at == 0) DBG(13);
      }
    }
  } else {
    asm volatile("setmaxnreg.dec.sync.aligned.u32 32;");
    if (tid == 384) {
      reinterpret_cast<uint32_t*>(smem + OFF_VAR)[0] = 0; reinterpret_cast<uint32_t*>(smem + OFF_VAR)[1] = ~0u;
      mbar_expect_tx(bar + B_PA * 8, 65536);
#pragma unroll
      for (int ec = 0; ec < 4; ec++) tma_load_2d(sb + OFF_A + ec * 8192, &tm_wq, h * DH + ec * 64, 64 * j, bar + B_PA * 8);
      tma_load_2d(sb + OFF_A + 32768, &tm_wo, 64 * j, h * DH, bar + B_PA * 8);
      for (int i = 0; i < 16; i++) {
        const int st = i % 5, half = i >> 3, ec = (i & 7) >> 1;
        if (i >= 5) mbar_wait(bar + (B_PE5 + st) * 8, ((i / 5) - 1) & 1);
        mbar_expect_tx(bar + (B_PF + i) * 8, XT_BYTES);
        tma_load_2d(sb + OFF_B + st * XT_BYTES, (i & 1) ? &tm_wv : &tm_wk, h * DH + ec * 64, half * 224, bar + (B_PF + i) * 8);
      }
    }
    if (tid == 384) {
#pragma unroll 1
      for (int sg = 0; sg < 2; sg++) {
        mbar_wait(bar + (B_PE5 + 3 + sg) * 8, 0);
        mbar_expect_tx(bar + (B_XF + sg) * 8, XT_BYTES);
        tma_load_3d(sb + xstage_off(sg), &tm_x3, 0, sg * SEG, 0, bar + (B_XF + sg) * 8);
      }
    }
    if (warp == 13 && !(lane & 1)) {
      const int l8 = lane >> 2, v = lane & 3;
      const int c = 16 * (h >> 2) + 2 * (h & 3) + (l8 >> 2) + (v >> 1) * 8;
      for (int s = 1; s < NSEG; s++) st_relaxed(args.Mg + (size_t)s * 1792 + (64 * j + c) * 4 + (l8 & 3), 0xFFFFFFFFu);
      __threadfence();
    }
    __syncwarp();
    named_bar(0, CHAIN_THREADS);
    if (CL) cluster_sync_all();
    if (tid == 384) {
      issue_x_load<CL>(sb, &tm_x, &tm_x3, 2, h); issue_x_load<CL>(sb, &tm_x, &tm_x3, 3, h);
      for (int s = 0; s < NSEG; s++) {
        mbar_wait(bar + (B_ST + (s & 3)) * 8, (s >> 2) & 1);
        tma_store_2d(&tm_k, 64 * j, (h * NSEG + s) * LKEY, sb + OFF_A + (s & 3) * STG_BYTES);
        mbar_wait(bar + (B_ST + 4 + (s & 3)) * 8, (s >> 2) & 1);
        tma_store_2d(&tm_y, 64 * j, (h * NSEG + s) * LKEY, sb + OFF_A + (4 + (s & 3)) * STG_BYTES);
        bulk_commit();
        if (s + 4 < NSEG) issue_x_load<CL>(sb, &tm_x, &tm_x3, s + 4, h);
        bulk_wait<0>();
        fence_async_all();
        __threadfence();
        red_u32(args.flag + s, 1u);
      }
    } else if (warp == 13) {
      for (int s = 0; s < NSEG - 1; s++) {
        float acc;
        if (CL && lane == 0) mbar_expect_tx(bar + (B_PB + (s & 1)) * 8, 16 * 128);
        poll_smm(smem, bar, args.Sg + (((size_t)s * NH + h) * 5 + 4) * 32 + lane, s, 1, lane);
        if (CL) {
          mbar_wait_cluster(bar + (B_PB + (s & 1)) * 8, (s >> 1) & 1);
          if (lane == 0) DBG(5);
          const float* pin = reinterpret_cast<const float*>(smem + OFF_P + (s & 1) * 2048);
          float a0 = 0.f, a1 = 0.f, a2 = 0.f, a3 = 0.f;
#pragma unroll
          for (int k = 0; k < 16; k += 4) { a0 += pin[k * 32 + lane]; a1 += pin[(k + 1) * 32 + lane]; a2 += pin[(k + 2) * 32 + lane]; a3 += pin[(k + 3) * 32 + lane]; }
          acc = (a0 + a1) + (a2 + a3);
        } else {
          const uint32_t* src = reinterpret_cast<const uint32_t*>(args.Sg + (size_t)NSEG * NH * 5 * 32) + (((size_t)s * NJ + j) * 16 + h) * 16 * 32 + lane;
          acc = 0.f;
#pragma unroll 1
          for (int k = 0; k < 16; k += 4) {
            uint32_t v0, v1, v2, v3; int it = 0;
            do {
              asm volatile("ld.volatile.global.u32 %0, [%1];" : "=r"(v0) : "l"(src + k * 32) : "memory");
              asm volatile("ld.volatile.global.u32 %0, [%1];" : "=r"(v1) : "l"(src + k * 32 + 32) : "memory");
              asm volatile("ld.volatile.global.u32 %0, [%1];" : "=r"(v2) : "l"(src + k * 32 + 64) : "memory");
              asm volatile("ld.volatile.global.u32 %0, [%1];" : "=r"(v3) : "l"(src + k * 32 + 96) : "memory");
            } while ((v0 == 0u || v1 == 0u || v2 == 0u || v3 == 0u) && ++it < SPIN_LIMIT);
            acc += (__uint_as_float(~v0) + __uint_as_float(~v1)) + (__uint_as_float(~v2) + __uint_as_float(~v3));
            uint32_t* cl = const_cast<uint32_t*>(src) + k * 32;
            cl[0] = 0u; cl[32] = 0u; cl[64] = 0u; cl[96] = 0u;
          }
        }
        const float o = __shfl_down_sync(~0u, acc, 1);
        const uint32_t u = pack_bf16(acc, o);
        const int l8 = lane >> 2, v = lane & 3;
        const int c = 16 * (h >> 2) + 2 * (h & 3) + (l8 >> 2) + (v >> 1) * 8;
        if (!(lane & 1)) st_relaxed(args.Mg + (size_t)(s + 1) * 1792 + (64 * j + c) * 4 + (l8 & 3), u);
        if (lane == 0) { DBG(6); mbar_arrive(bar + (B_RD + (s & 1)) * 8); }
      }
    } else if (warp == 15) {
      for (int s = 0; s < NSEG - 1; s++) poll_smm(smem, bar, args.Sg + (((size_t)s * NH + h) * 5 + 4) * 32 + lane, s, 0, lane);
    } else if (tid == 448) {
      volatile uint32_t* var = reinterpret_cast<volatile uint32_t*>(smem + OFF_VAR);
      uint32_t n = 0, empar = 0;
      for (int s = 0; s < NSEG; s++) {
        if (s > 0) mbar_wait(bar + (B_RD + ((s - 1) & 1)) * 8, ((s - 1) >> 1) & 1);
        const uint32_t n0 = n;
        var[3] = n0;
        mbar_arrive(bar + B_SB * 8);
        uint32_t tnext = clk32() + MD0;
        int it = 0;
        if (s == 0) n = 1;
        while (s > 0) {
          bool done = false;
          while ((int)(clk32() - tnext) < 0) { if (var[1] == (uint32_t)s) { done = true; break; } }
          if (done || var[1] == (uint32_t)s || ++it > SPIN_LIMIT) break;
          const int slot = n & 3;
          if (n - n0 >= 4) {
            int it2 = 0;
            while (!mbar_test(bar + (B_EM + slot) * 8, (empar >> slot) & 1)) { if (var[1] == (uint32_t)s || ++it2 > SPIN_LIMIT) { done = true; break; } }
            if (done) break;
            empar ^= 1u << slot;
          }
          mbar_expect_tx(bar + (B_MF + slot) * 8, 7168);
          bulk_load(sb + mslot_off(slot), args.Mg + (size_t)s * 1792, 7168, bar + (B_MF + slot) * 8);
          n++;
          tnext += MDELTA;
        }
        { int it3 = 0; while (var[1] != (uint32_t)s && ++it3 < SPIN_LIMIT) {} }
        const uint32_t ns = var[2];
        const uint32_t waited = n - n0 > 4 ? n - n0 - 4 : 0;
        for (uint32_t a = n0 + waited; a < ns; a++) empar ^= 1u << (a & 3);
        for (uint32_t a = ns + 1; a < n; a++) mbar_wait(bar + (B_MF + (a & 3)) * 8, (a >> 2) & 1);
        reinterpret_cast<uint32_t*>(smem + OFF_DBG)[s * 16 + 15] = n - n0;
      }
    }
    __syncwarp();
  }
  named_bar(0, CHAIN_THREADS);
  KT_END(0);
  if (CL) cluster_sync_all();
}
struct SsmArgs {
  const bf16 *lam_re, *lam_im, *log_dt, *dskip, *x, *gate_w;
  float* hloc;
  float2* hend;
  float* omg;
  float* out;
};

__device__ __forceinline__ float bf2f(bf16 v) { return __bfloat162float(v); }
__device__ __forceinline__ float rbf(float v) { return __bfloat162float(__float2bfloat16_rn(v)); }
__device__ __forceinline__ float2 cmul(float2 a, float2 b) { return make_float2(a.x * b.x - a.y * b.y, a.x * b.y + a.y * b.x); }
__device__ __forceinline__ float2 ssm_z(const SsmArgs& a, int ch) {
  const float dt = rbf(expf(bf2f(a.log_dt[ch])));
  return make_float2(dt * bf2f(a.lam_re[ch]), dt * bf2f(a.lam_im[ch]));
}
__device__ __forceinline__ float2 cexp_n(float2 z, float n) {
  float sn, cs;
  sincosf(z.y * n, &sn, &cs);
  const float e = expf(z.x * n);
  return make_float2(e * cs, e * sn);
}

constexpr int S1_STAGE = 32768, S1_NST = 3, S1_SMEM = S1_NST * S1_STAGE + 256;
__global__ void __launch_bounds__(160, 2)
ssm1_kernel(const __grid_constant__ CUtensorMap tm_bre, const __grid_constant__ CUtensorMap tm_bim, const __grid_constant__ CUtensorMap tm_xp, SsmArgs args) {
  extern __shared__ __align__(1024) uint8_t smem[];
  const uint32_t sb = smem_u32(smem), bar = sb + S1_NST * S1_STAGE;
  const int tid = threadIdx.x, warp = tid >> 5, lane = tid & 31;
  const int cg = blockIdx.x, tc = blockIdx.y;
  KT_START(1);
  if (tid == 0) {
    for (int i = 0; i < 7; i++) mbar_init(bar + i * 8, 1);
    for (int i = 0; i < 3; i++) mbar_init(bar + (8 + i) * 8, 4);
    asm volatile("fence.mbarrier_init.release.cluster;" ::: "memory");
  }
  __syncthreads();
  if (warp == 4) {
    if (lane == 0) {
      for (int kc = 0; kc < 7; kc++) {
        const int st = kc % 3;
        if (kc >= 3) mbar_wait(bar + (8 + st) * 8, ((kc / 3) - 1) & 1);
        mbar_expect_tx(bar + kc * 8, S1_STAGE);
        tma_load_2d(sb + st * S1_STAGE, &tm_bre, kc * 64, cg * 64, bar + kc * 8);
        tma_load_2d(sb + st * S1_STAGE + 8192, &tm_bim, kc * 64, cg * 64, bar + kc * 8);
        tma_load_4d(sb + st * S1_STAGE + 16384, &tm_xp, kc * 64, 0, tc * 4, 0, bar + kc * 8);
      }
    }
    return;
  }
  const int g = lane >> 2, q = lane & 3;
  float2 zz[2]; float lre[2], lim[2];
#pragma unroll
  for (int r = 0; r < 2; r++) { const int ch = cg * 64 + warp * 16 + g + r * 8; zz[r] = ssm_z(args, ch); lre[r] = bf2f(args.lam_re[ch]); lim[r] = bf2f(args.lam_im[ch]); }
  float ur[64], ui[64];
#pragma unroll 1
  for (int kc = 0; kc < 7; kc++) {
    const int st = kc % 3;
    mbar_wait(bar + kc * 8, 0);
    const uint32_t b0 = sb + st * S1_STAGE;
    wg_fence();
#pragma unroll
    for (int kk = 0; kk < 4; kk++) {
      wgmma_ss_n128(ur, desc_sw128(b0 + kk * 32), desc_sw128(b0 + 16384 + kk * 32), (kc | kk) != 0);
      wgmma_ss_n128(ui, desc_sw128(b0 + 8192 + kk * 32), desc_sw128(b0 + 16384 + kk * 32), (kc | kk) != 0);
    }
    wg_commit();
    wg_wait<0>();
    if (lane == 0) mbar_arrive(bar + (8 + st) * 8);
  }
#pragma unroll
  for (int r = 0; r < 2; r++) {
    const int ch = cg * 64 + warp * 16 + g + r * 8;
    const float2 z = zz[r];
    const float2 lam = cexp_n(z, 1.f);
    const float lr = lre[r], li = lim[r];
    const float den = lr * lr + li * li;
    const float2 num = make_float2(lam.x - 1.f, lam.y);
    const float2 coef = make_float2((num.x * lr + num.y * li) / den, (num.y * lr - num.x * li) / den);
    float2 hs = make_float2(0.f, 0.f);
#pragma unroll
    for (int i = 0; i < 32; i++) {
      const int idx = (i >> 1) * 4 + r * 2 + (i & 1);
      const float2 bu = cmul(coef, make_float2(ur[idx], ui[idx]));
      hs = make_float2(fmaf(lam.x, hs.x, fmaf(-lam.y, hs.y, bu.x)), fmaf(lam.x, hs.y, fmaf(lam.y, hs.x, bu.y)));
      ur[idx] = hs.x; ui[idx] = hs.y;
    }
    const float2 l32 = cexp_n(z, 32.f);
    float2 carry = make_float2(0.f, 0.f);
#pragma unroll
    for (int qq = 0; qq < 3; qq++) {
      const float ex = __shfl_sync(~0u, hs.x, (lane & ~3) + qq), ey = __shfl_sync(~0u, hs.y, (lane & ~3) + qq);
      if (qq < q) { const float2 t = cmul(l32, carry); carry = make_float2(t.x + ex, t.y + ey); }
    }
    float2 p = lam;
    float4* dre = reinterpret_cast<float4*>(args.hloc) + ((((size_t)tc * 7 + cg) * 4 + warp) * 2 + r) * 256 + lane;
    float4* dim = dre + (size_t)DM * SEQ / 4;
#pragma unroll
    for (int i4 = 0; i4 < 8; i4++) {
      float vr[4], vi[4];
#pragma unroll
      for (int e = 0; e < 4; e++) {
        const int i = i4 * 4 + e, idx = (i >> 1) * 4 + r * 2 + (i & 1);
        const float2 t = cmul(p, carry);
        vr[e] = ur[idx] + t.x; vi[e] = ui[idx] + t.y;
        p = cmul(p, lam);
      }
      dre[i4 * 32] = make_float4(vr[0], vr[1], vr[2], vr[3]);
      dim[i4 * 32] = make_float4(vi[0], vi[1], vi[2], vi[3]);
      if (i4 == 7 && q == 3) args.hend[tc * DM + ch] = make_float2(vr[3], vi[3]);
    }
  }
  KT_END(1);
}

constexpr int S2_A = 896 * 128, S2_NST = 3, S2_SMEM = S2_A + S2_NST * XT_BYTES + 1024;
__global__ void __launch_bounds__(288, 1)
ssm2_kernel(const __grid_constant__ CUtensorMap tm_cre, const __grid_constant__ CUtensorMap tm_cim, SsmArgs args) {
  extern __shared__ __align__(1024) uint8_t smem[];
  const uint32_t sb = smem_u32(smem), bar = sb + S2_A + S2_NST * XT_BYTES;
  float* sg = reinterpret_cast<float*>(smem + S2_A + S2_NST * XT_BYTES + 512);
  const int tid = threadIdx.x, warp = tid >> 5, lane = tid & 31;
  const int t0 = blockIdx.x * 64, chunk = t0 >> 7, tau0 = t0 & 127;
  KT_START(2);
  if (tid == 0) {
    for (int i = 0; i < 28; i++) mbar_init(bar + i * 8, 1);
    for (int i = 0; i < 3; i++) mbar_init(bar + (28 + i) * 8, 4);
    asm volatile("fence.mbarrier_init.release.cluster;" ::: "memory");
  }
  __syncthreads();
  if (warp == 8) {
    if (lane == 0) {
      for (int i = 0; i < 28; i++) {
        const int st = i % 3, kc = i >> 1;
        if (i >= 3) mbar_wait(bar + (28 + st) * 8, ((i / 3) - 1) & 1);
        mbar_expect_tx(bar + i * 8, XT_BYTES);
        tma_load_2d(sb + S2_A + st * XT_BYTES, kc < 7 ? &tm_cre : &tm_cim, (kc % 7) * 64, (i & 1) * 224, bar + i * 8);
      }
    }
    return;
  }
  {
    float acc[8];
#pragma unroll
    for (int tt = 0; tt < 8; tt++) acc[tt] = 0.f;
#pragma unroll
    for (int d = 2 * lane; d < DM; d += 64) {
      const __nv_bfloat162 wv = *reinterpret_cast<const __nv_bfloat162*>(args.gate_w + d);
#pragma unroll
      for (int tt = 0; tt < 8; tt++) {
        const __nv_bfloat162 xv = *reinterpret_cast<const __nv_bfloat162*>(args.x + (size_t)(t0 + warp * 8 + tt) * DM + d);
        acc[tt] += rbf(bf2f(xv.x) * bf2f(wv.x)) + rbf(bf2f(xv.y) * bf2f(wv.y));
      }
    }
#pragma unroll
    for (int tt = 0; tt < 8; tt++) {
#pragma unroll
      for (int o = 16; o; o >>= 1) acc[tt] += __shfl_xor_sync(~0u, acc[tt], o);
      if (lane == 0) {
        const float gv = rbf(1.f / (1.f + expf(-rbf(acc[tt]))));
        sg[warp * 8 + tt] = gv;
        args.omg[t0 + warp * 8 + tt] = rbf(1.f - gv);
      }
    }
  }
  for (int it = tid; it < DM * 2; it += 256) {
    const int qi = it & 1, gg = (it >> 1) & 7, r = (it >> 4) & 1, cw = it >> 5;
    const int ch = cw * 16 + r * 8 + gg;
    const float2 z = ssm_z(args, ch);
    float2 e[15];
#pragma unroll
    for (int c = 0; c < 15; c++) e[c] = c < chunk ? args.hend[c * DM + ch] : make_float2(0.f, 0.f);
    const int qq = (tau0 >> 5) + qi;
    const float4* sre = reinterpret_cast<const float4*>(args.hloc) + (((size_t)chunk * 28 + cw) * 2 + r) * 256 + gg * 4 + qq;
    const float4* sim = sre + (size_t)DM * SEQ / 4;
    float4 vr4[8], vi4[8];
#pragma unroll
    for (int i4 = 0; i4 < 8; i4++) { vr4[i4] = sre[i4 * 32]; vi4[i4] = sim[i4 * 32]; }
    const float2 l128 = cexp_n(z, 128.f);
    float2 hin = make_float2(0.f, 0.f);
#pragma unroll
    for (int c = 0; c < 15; c++) if (c < chunk) { const float2 t = cmul(l128, hin); hin = make_float2(t.x + e[c].x, t.y + e[c].y); }
    const float2 lam = cexp_n(z, 1.f);
    float2 p = cmul(cexp_n(z, (float)(qq * 32 + 1)), hin);
#pragma unroll
    for (int m = 0; m < 4; m++) {
      float vr[8] = {vr4[2 * m].x, vr4[2 * m].y, vr4[2 * m].z, vr4[2 * m].w, vr4[2 * m + 1].x, vr4[2 * m + 1].y, vr4[2 * m + 1].z, vr4[2 * m + 1].w};
      float vi[8] = {vi4[2 * m].x, vi4[2 * m].y, vi4[2 * m].z, vi4[2 * m].w, vi4[2 * m + 1].x, vi4[2 * m + 1].y, vi4[2 * m + 1].z, vi4[2 * m + 1].w};
#pragma unroll
      for (int k = 0; k < 8; k++) { vr[k] = 2.f * (vr[k] + p.x); vi[k] = -2.f * (vi[k] + p.y); p = cmul(p, lam); }
      const uint4 pr = make_uint4(pack_bf16(vr[0], vr[1]), pack_bf16(vr[2], vr[3]), pack_bf16(vr[4], vr[5]), pack_bf16(vr[6], vr[7]));
      const uint4 pi = make_uint4(pack_bf16(vi[0], vi[1]), pack_bf16(vi[2], vi[3]), pack_bf16(vi[4], vi[5]), pack_bf16(vi[6], vi[7]));
      const int m8 = qi * 4 + m;
      *reinterpret_cast<uint4*>(smem + ch * 128 + ((m8 ^ (ch & 7)) << 4)) = pr;
      *reinterpret_cast<uint4*>(smem + (DM + ch) * 128 + ((m8 ^ (ch & 7)) << 4)) = pi;
    }
  }
  fence_async_smem();
  named_bar(1, 256);
  const int wg = warp >> 2, w = warp & 3;
  float acc[112];
#pragma unroll 1
  for (int kc = 0; kc < 14; kc++) {
    const int i = kc * 2 + wg, st = i % 3;
    mbar_wait(bar + i * 8, 0);
    const uint32_t bb = sb + S2_A + st * XT_BYTES;
    wg_fence();
#pragma unroll
    for (int kk = 0; kk < 4; kk++) {
      const uint64_t da = desc_sw128(sb + (kc * 64 + kk * 16) * 128);
      wgmma_ss_n112_ta(acc, da, desc_sw128(bb + kk * 32), (kc | kk) != 0);
      wgmma_ss_n112_ta(acc + 56, da, desc_sw128(bb + 14336 + kk * 32), (kc | kk) != 0);
    }
    wg_commit();
    wg_wait<0>();
    if (lane == 0) mbar_arrive(bar + (28 + st) * 8);
  }
  const int g = lane >> 2, q = lane & 3;
  named_bar(1, 256);
  float* stg = reinterpret_cast<float*>(smem);
#pragma unroll
  for (int r = 0; r < 2; r++)
#pragma unroll
    for (int nt = 0; nt < 28; nt++)
      *reinterpret_cast<float2*>(stg + (w * 16 + g + r * 8) * 456 + wg * 224 + nt * 8 + 2 * q) = make_float2(acc[nt * 4 + r * 2], acc[nt * 4 + r * 2 + 1]);
  named_bar(1, 256);
  for (int it = tid; it < 64 * 112; it += 256) {
    const int tl = it / 112, d = (it % 112) * 4;
    const float4 y = *reinterpret_cast<const float4*>(stg + tl * 456 + d);
    const uint2 xu = *reinterpret_cast<const uint2*>(args.x + (size_t)(t0 + tl) * DM + d), du = *reinterpret_cast<const uint2*>(args.dskip + d);
    const float gv = sg[tl];
    float4 o;
    o.x = gv * (y.x + rbf(__uint_as_float(xu.x << 16) * __uint_as_float(du.x << 16)));
    o.y = gv * (y.y + rbf(__uint_as_float(xu.x & 0xFFFF0000u) * __uint_as_float(du.x & 0xFFFF0000u)));
    o.z = gv * (y.z + rbf(__uint_as_float(xu.y << 16) * __uint_as_float(du.y << 16)));
    o.w = gv * (y.w + rbf(__uint_as_float(xu.y & 0xFFFF0000u) * __uint_as_float(du.y & 0xFFFF0000u)));
    *reinterpret_cast<float4*>(args.out + (size_t)(t0 + tl) * DM + d) = o;
  }
  KT_END(2);
}
struct AttnArgs {
  uint32_t* flag;
  uint32_t* ticket;
  const float* omg;
  float* out;
};
constexpr int AT_SPLIT = 60;
constexpr int AT_ITEMS = AT_SPLIT * 4 + (NSEG - AT_SPLIT) * 8;
constexpr int AT_X = 2 * 7 * 4096;
constexpr int AT_T = 7 * 5120;
constexpr int AT_OFF_K = AT_X, AT_OFF_Y = AT_X + 2 * AT_T;
constexpr int AT_OFF_P = AT_X + 4 * AT_T;
constexpr int AT_OFF_BAR = AT_OFF_P + 2 * 2 * 64 * 48;
constexpr int AT_STG = 16 * 72 * 4;
constexpr int AT_OFF_STG = AT_OFF_BAR + 256;
constexpr int AT_SMEM = AT_OFF_STG + 4 * AT_STG;
constexpr uint32_t FLAG_TARGET = 112;

__device__ __forceinline__ void attn_decode(int item, int& s, int& p0, int& np) {
  if (item < AT_SPLIT * 4) { s = item >> 2; p0 = (item & 3) * 2; np = 2; }
  else { const int i = item - AT_SPLIT * 4; s = AT_SPLIT + (i >> 3); p0 = i & 7; np = 1; }
}

__device__ __forceinline__ void attn_consumer(uint8_t* smem, uint32_t sb, const AttnArgs& args, int wg, int w, int lane) {
  const uint32_t bar = sb + AT_OFF_BAR;
  volatile int* s_item = reinterpret_cast<volatile int*>(smem + AT_OFF_BAR + 128);
  float* stg = reinterpret_cast<float*>(smem + AT_OFF_STG + (wg * 2 + (w & 1)) * AT_STG);
  const int g = lane >> 2, q = lane & 3;
  const int C0 = wg * 4;
  int m = 0;
  for (int n = 0;; n++) {
    mbar_wait(bar + (0 + (n & 1)) * 8, (n >> 1) & 1);
    const int item = s_item[n & 1];
    if (item >= AT_ITEMS) break;
    int s, p0, np;
    attn_decode(item, s, p0, np);
    const uint64_t dx = desc_sw128(sb + (n & 1) * (7 * 4096));
    float acc[4][32];
#pragma unroll 1
    for (int pp = 0; pp < np; pp++, m++) {
      const uint64_t dk = desc_sw128(sb + AT_OFF_K + wg * AT_T);
      mbar_wait(bar + 4 * 8, m & 1);
      float sc[20];
      wg_fence();
#pragma unroll
      for (int kc = 0; kc < 7; kc++)
#pragma unroll
        for (int kk = 0; kk < 4; kk++) wgmma_ss_n40(sc, dx + (uint64_t)(kc * 256 + kk * 2), dk + (uint64_t)(kc * 320 + kk * 2), (kc | kk) != 0);
      wg_commit();
      wg_wait<0>();
      __syncwarp();
      if (lane == 0) { mbar_arrive(bar + 5 * 8); if (pp == np - 1) mbar_arrive(bar + (2 + (n & 1)) * 8); }
      uint32_t pa[2][12];
#pragma unroll
      for (int i = 0; i < 12; i++) { pa[0][i] = 0u; pa[1][i] = 0u; }
      uint8_t* pbuf = smem + AT_OFF_P + (m & 1) * (2 * 64 * 48);
      if (w < 2) {
#pragma unroll
        for (int r = 0; r < 2; r++) {
          const int t = w * 16 + g + r * 8;
          float v[10];
          float mx = -3.0e38f;
#pragma unroll
          for (int nt = 0; nt < 5; nt++)
#pragma unroll
            for (int e = 0; e < 2; e++) {
              const int key = nt * 8 + 2 * q + e;
              const float x = (key - NMEM <= t) ? sc[nt * 4 + r * 2 + e] : -1.0e9f;
              v[nt * 2 + e] = x; mx = fmaxf(mx, x);
            }
          mx = fmaxf(mx, __shfl_xor_sync(~0u, mx, 1));
          mx = fmaxf(mx, __shfl_xor_sync(~0u, mx, 2));
          float l = 0.f;
#pragma unroll
          for (int k = 0; k < 10; k++) { v[k] = ex2((v[k] - mx) * L2E); l += v[k]; }
          l += __shfl_xor_sync(~0u, l, 1);
          l += __shfl_xor_sync(~0u, l, 2);
          const float rl = 1.f / l;
          pa[0][r] = pack_bf16(v[0] * rl, v[1] * rl); pa[0][2 + r] = pack_bf16(v[2] * rl, v[3] * rl);
          pa[0][4 + r] = pack_bf16(v[4] * rl, v[5] * rl); pa[0][6 + r] = pack_bf16(v[6] * rl, v[7] * rl);
          pa[0][8 + r] = pack_bf16(v[8] * rl, v[9] * rl);
        }
        uint4* ps = reinterpret_cast<uint4*>(pbuf + (wg * 64 + w * 32 + lane) * 48);
        ps[0] = make_uint4(pa[0][0], pa[0][1], pa[0][2], pa[0][3]);
        ps[1] = make_uint4(pa[0][4], pa[0][5], pa[0][6], pa[0][7]);
        ps[2] = make_uint4(pa[0][8], pa[0][9], 0u, 0u);
      }
      named_bar(1, 256);
      if (w < 2) {
        const uint4* ps = reinterpret_cast<const uint4*>(pbuf + ((wg ^ 1) * 64 + w * 32 + lane) * 48);
        const uint4 u0 = ps[0], u1 = ps[1], u2 = ps[2];
        pa[1][0] = u0.x; pa[1][1] = u0.y; pa[1][2] = u0.z; pa[1][3] = u0.w; pa[1][4] = u1.x; pa[1][5] = u1.y; pa[1][6] = u1.z; pa[1][7] = u1.w;
        pa[1][8] = u2.x; pa[1][9] = u2.y;
      }
      const uint64_t dy0 = desc_sw128(sb + AT_OFF_Y + wg * AT_T), dy1 = desc_sw128(sb + AT_OFF_Y + (wg ^ 1) * AT_T);
      mbar_wait(bar + 6 * 8, m & 1);
      wg_fence();
#pragma unroll
      for (int c = 0; c < 4; c++) {
        const int cc = min(C0 + c, 6);
#pragma unroll
        for (int kk = 0; kk < 3; kk++) wgmma_rs_n64_tb(acc[c], &pa[0][kk * 4], dy0 + (uint64_t)(cc * 320 + kk * 128), (pp | kk) != 0);
#pragma unroll
        for (int kk = 0; kk < 3; kk++) wgmma_rs_n64_tb(acc[c], &pa[1][kk * 4], dy1 + (uint64_t)(cc * 320 + kk * 128), 1);
      }
      wg_commit();
      wg_wait<0>();
      __syncwarp();
      if (lane == 0) mbar_arrive(bar + 7 * 8);
    }
    if (w < 2) {
      const float om0 = args.omg[s * SEG + w * 16 + g], om1 = args.omg[s * SEG + w * 16 + g + 8];
#pragma unroll
      for (int c = 0; c < 4; c++) {
        if (C0 + c < 7) {
#pragma unroll
          for (int nt = 0; nt < 8; nt++) {
            *reinterpret_cast<float2*>(stg + g * 72 + nt * 8 + 2 * q) = make_float2(om0 * acc[c][nt * 4], om0 * acc[c][nt * 4 + 1]);
            *reinterpret_cast<float2*>(stg + (g + 8) * 72 + nt * 8 + 2 * q) = make_float2(om1 * acc[c][nt * 4 + 2], om1 * acc[c][nt * 4 + 3]);
          }
          __syncwarp();
#pragma unroll 2
          for (int i = 0; i < 8; i++) {
            const int row = i * 2 + (lane >> 4), col = (lane & 15) * 4;
            const float4 v = *reinterpret_cast<const float4*>(stg + row * 72 + col);
            red_v4(args.out + (size_t)(s * SEG + w * 16 + row) * DM + (C0 + c) * 64 + col, v.x, v.y, v.z, v.w);
          }
          __syncwarp();
        }
      }
    }
  }
}

__global__ void __launch_bounds__(384, 1)
attn_kernel(const __grid_constant__ CUtensorMap tm_x, const __grid_constant__ CUtensorMap tm_k, const __grid_constant__ CUtensorMap tm_y, AttnArgs args) {
  extern __shared__ __align__(1024) uint8_t smem[];
  const uint32_t sb = smem_u32(smem), bar = sb + AT_OFF_BAR;
  volatile int* s_item = reinterpret_cast<volatile int*>(smem + AT_OFF_BAR + 128);
  const int tid = threadIdx.x, warp = tid >> 5, lane = tid & 31;
  KT_START(3);
  if (tid == 0) {
    mbar_init(bar + 0 * 8, 1); mbar_init(bar + 1 * 8, 1); mbar_init(bar + 2 * 8, 8); mbar_init(bar + 3 * 8, 8);
    mbar_init(bar + 4 * 8, 1); mbar_init(bar + 5 * 8, 8); mbar_init(bar + 6 * 8, 1); mbar_init(bar + 7 * 8, 8);
    asm volatile("fence.mbarrier_init.release.cluster;" ::: "memory");
  }
  for (int i = tid; i < AT_OFF_BAR / 16; i += 384) *reinterpret_cast<uint4*>(smem + i * 16) = make_uint4(0, 0, 0, 0);
  fence_async_smem();
  __syncthreads();
  const int wg = __shfl_sync(0xffffffffu, warp >> 2, 0);
  if (wg == 2) {
    asm volatile("setmaxnreg.dec.sync.aligned.u32 40;");
    if (tid == 256) {
      int m = 0;
      for (int n = 0;; n++) {
        const int sl = n & 1;
        if (n >= 2) mbar_wait(bar + (2 + sl) * 8, ((n >> 1) - 1) & 1);
        const int item = (int)atomicAdd(args.ticket, 1u);
        s_item[sl] = item;
        if (item >= AT_ITEMS) {
          mbar_arrive(bar + sl * 8);
          if (atomicAdd(args.ticket + 1, 1u) == gridDim.x - 1) {
            for (int i = 0; i < NSEG; i++) args.flag[i] = 0u;
            args.ticket[0] = 0u; args.ticket[1] = 0u;
          }
          break;
        }
        int s, p0, np;
        attn_decode(item, s, p0, np);
        mbar_expect_tx(bar + sl * 8, 7 * 4096);
        tma_load_3d(sb + sl * (7 * 4096), &tm_x, 0, s * SEG, 0, bar + sl * 8);
        { int it = 0; while (ld_acquire(args.flag + s) < FLAG_TARGET && ++it < SPIN_LIMIT) __nanosleep(100); }
        fence_async_all();
        for (int pp = 0; pp < np; pp++, m++) {
          const int row = (((p0 + pp) * 2) * NSEG + s) * LKEY;
          if (m >= 1) mbar_wait(bar + 5 * 8, (m - 1) & 1);
          mbar_expect_tx(bar + 4 * 8, 2 * AT_T);
          tma_load_3d(sb + AT_OFF_K, &tm_k, 0, row, 0, bar + 4 * 8);
          tma_load_3d(sb + AT_OFF_K + AT_T, &tm_k, 0, row + NSEG * LKEY, 0, bar + 4 * 8);
          if (m >= 1) mbar_wait(bar + 7 * 8, (m - 1) & 1);
          mbar_expect_tx(bar + 6 * 8, 2 * AT_T);
          tma_load_3d(sb + AT_OFF_Y, &tm_y, 0, row, 0, bar + 6 * 8);
          tma_load_3d(sb + AT_OFF_Y + AT_T, &tm_y, 0, row + NSEG * LKEY, 0, bar + 6 * 8);
        }
      }
    }
  } else {
    asm volatile("setmaxnreg.inc.sync.aligned.u32 232;");
    attn_consumer(smem, sb, args, wg, warp & 3, lane);
    KT_END(3);
  }
}
__device__ bf16 g_Kall[(size_t)NH * NSEG * LKEY * DM];
__device__ bf16 g_Yall[(size_t)NH * NSEG * LKEY * DM];
__device__ uint32_t g_M[65 * 1792];
__device__ float4 g_S[(size_t)NSEG * NH * 5 * 32 + (size_t)NSEG * NJ * 16 * 16 * 8];
__device__ uint32_t g_flag[NSEG + 64];
__device__ float g_hloc[2 * DM * SEQ];
__device__ float2 g_hend[16 * DM];
__device__ float g_omg[SEQ];
__device__ uint32_t g_dbg[112 * 1024 + 112 * 4];

typedef CUresult (*EncodeFn)(CUtensorMap*, CUtensorMapDataType, cuuint32_t, void*, const cuuint64_t*, const cuuint64_t*, const cuuint32_t*,
                             const cuuint32_t*, CUtensorMapInterleave, CUtensorMapSwizzle, CUtensorMapL2promotion, CUtensorMapFloatOOBfill);

static bool make_map_2d(EncodeFn enc, CUtensorMap* m, const void* ptr, uint64_t cols, uint64_t rows, uint32_t box_cols, uint32_t box_rows) {
  cuuint64_t dims[2] = {cols, rows};
  cuuint64_t strides[1] = {cols * 2};
  cuuint32_t box[2] = {box_cols, box_rows};
  cuuint32_t es[2] = {1, 1};
  return enc(m, CU_TENSOR_MAP_DATA_TYPE_BFLOAT16, 2, const_cast<void*>(ptr), dims, strides, box, es, CU_TENSOR_MAP_INTERLEAVE_NONE,
             CU_TENSOR_MAP_SWIZZLE_128B, CU_TENSOR_MAP_L2_PROMOTION_L2_256B, CU_TENSOR_MAP_FLOAT_OOB_FILL_NONE) == CUDA_SUCCESS;
}
static bool make_map_rows(EncodeFn enc, CUtensorMap* m, const void* ptr, uint64_t rows, uint32_t box_rows) {
  cuuint64_t dims[3] = {64, rows, 7};
  cuuint64_t strides[2] = {(cuuint64_t)DM * 2, 128};
  cuuint32_t box[3] = {64, box_rows, 7};
  cuuint32_t es[3] = {1, 1, 1};
  return enc(m, CU_TENSOR_MAP_DATA_TYPE_BFLOAT16, 3, const_cast<void*>(ptr), dims, strides, box, es, CU_TENSOR_MAP_INTERLEAVE_NONE,
             CU_TENSOR_MAP_SWIZZLE_128B, CU_TENSOR_MAP_L2_PROMOTION_L2_256B, CU_TENSOR_MAP_FLOAT_OOB_FILL_NONE) == CUDA_SUCCESS;
}
static bool make_map_xperm(EncodeFn enc, CUtensorMap* m, const void* ptr) {
  cuuint64_t dims[4] = {(cuuint64_t)DM, 2, 64, 16};
  cuuint64_t strides[3] = {(cuuint64_t)DM * 2, (cuuint64_t)DM * 2 * 32, (cuuint64_t)DM * 2 * 2};
  cuuint32_t box[4] = {64, 2, 4, 16};
  cuuint32_t es[4] = {1, 1, 1, 1};
  return enc(m, CU_TENSOR_MAP_DATA_TYPE_BFLOAT16, 4, const_cast<void*>(ptr), dims, strides, box, es, CU_TENSOR_MAP_INTERLEAVE_NONE,
             CU_TENSOR_MAP_SWIZZLE_128B, CU_TENSOR_MAP_L2_PROMOTION_L2_256B, CU_TENSOR_MAP_FLOAT_OOB_FILL_NONE) == CUDA_SUCCESS;
}

struct HostState {
  bool init, ok, use_cluster;
  CUtensorMap tx, tq, tk, tv, to, tka, tya, tbre, tbim, txp, tcre, tcim, tx3, tk3, ty3;
  void *pK, *pY, *pM, *pS, *pF, *pD, *pH, *pE, *pO;
  cudaStream_t side;
  cudaEvent_t ev_start, ev_join;
  int n_free;
  const void* key[17];
  void* key_out;
};
static HostState g_hs;

}

extern "C" void kernel_launch(void* const* d_in, const int* in_sizes, int n_in, void* d_out, int out_size) {
  HostState& S = g_hs;
  (void)in_sizes; (void)n_in; (void)out_size;
  cudaStream_t st = cudaStreamPerThread;
  bool same = S.init;
  for (int i = 0; i < 17 && same; i++) same = S.key[i] == d_in[i];
  if (!same) {
    EncodeFn enc = nullptr;
    cudaDriverEntryPointQueryResult qr;
    cudaGetDriverEntryPoint("cuTensorMapEncodeTiled", (void**)&enc, cudaEnableDefault, &qr);
    cudaGetSymbolAddress(&S.pK, g_Kall); cudaGetSymbolAddress(&S.pY, g_Yall); cudaGetSymbolAddress(&S.pM, g_M); cudaGetSymbolAddress(&S.pS, g_S);
    cudaGetSymbolAddress(&S.pF, g_flag); cudaGetSymbolAddress(&S.pD, g_dbg); cudaGetSymbolAddress(&S.pH, g_hloc); cudaGetSymbolAddress(&S.pE, g_hend);
    cudaGetSymbolAddress(&S.pO, g_omg);
    S.ok = enc && make_map_2d(enc, &S.tx, d_in[0], DM, SEQ, 64, 32) && make_map_2d(enc, &S.tq, d_in[11], 4096, DM, 64, 64) &&
           make_map_2d(enc, &S.tk, d_in[12], 4096, DM, 64, 224) && make_map_2d(enc, &S.tv, d_in[13], 4096, DM, 64, 224) &&
           make_map_2d(enc, &S.to, d_in[14], DM, 4096, 64, 256) && make_map_2d(enc, &S.tka, S.pK, DM, NH * NSEG * LKEY, 64, LKEY) &&
           make_map_2d(enc, &S.tya, S.pY, DM, NH * NSEG * LKEY, 64, LKEY) && make_map_2d(enc, &S.tbre, d_in[3], DM, DM, 64, 64) &&
           make_map_2d(enc, &S.tbim, d_in[4], DM, DM, 64, 64) && make_map_xperm(enc, &S.txp, d_in[0]) &&
           make_map_2d(enc, &S.tcre, d_in[5], DM, DM, 64, 224) && make_map_2d(enc, &S.tcim, d_in[6], DM, DM, 64, 224) &&
           make_map_rows(enc, &S.tx3, d_in[0], SEQ, SEG) && make_map_rows(enc, &S.tk3, S.pK, NH * NSEG * LKEY, LKEY) && make_map_rows(enc, &S.ty3, S.pY, NH * NSEG * LKEY, LKEY);
    if (!S.init) {
      cudaFuncSetAttribute(chain_kernel<true>, cudaFuncAttributeMaxDynamicSharedMemorySize, SMEM_CHAIN);
      cudaFuncSetAttribute(chain_kernel<true>, cudaFuncAttributeNonPortableClusterSizeAllowed, 1);
      cudaFuncSetAttribute(chain_kernel<false>, cudaFuncAttributeMaxDynamicSharedMemorySize, SMEM_CHAIN);
      cudaFuncSetAttribute(ssm1_kernel, cudaFuncAttributeMaxDynamicSharedMemorySize, S1_SMEM);
      cudaFuncSetAttribute(ssm2_kernel, cudaFuncAttributeMaxDynamicSharedMemorySize, S2_SMEM);
      cudaFuncSetAttribute(attn_kernel, cudaFuncAttributeMaxDynamicSharedMemorySize, AT_SMEM);
      cudaLaunchConfig_t cfg = {};
      cfg.gridDim = dim3(112); cfg.blockDim = dim3(CHAIN_THREADS); cfg.dynamicSmemBytes = SMEM_CHAIN;
      cudaLaunchAttribute at[1];
      at[0].id = cudaLaunchAttributeClusterDimension; at[0].val.clusterDim.x = 16; at[0].val.clusterDim.y = 1; at[0].val.clusterDim.z = 1;
      cfg.attrs = at; cfg.numAttrs = 1;
      int nc = 0;
      if (cudaOccupancyMaxActiveClusters(&nc, chain_kernel<true>, &cfg) != cudaSuccess) { nc = 0; (void)cudaGetLastError(); }
      S.use_cluster = nc >= 7;
      int sms = 132;
      cudaDeviceGetAttribute(&sms, cudaDevAttrMultiProcessorCount, 0);
      S.n_free = sms - 112 > 1 ? sms - 112 : 1;
      cudaStreamCreateWithFlags(&S.side, cudaStreamNonBlocking);
      cudaEventCreateWithFlags(&S.ev_start, cudaEventDisableTiming);
      cudaEventCreateWithFlags(&S.ev_join, cudaEventDisableTiming);
    }
    for (int i = 0; i < 17; i++) S.key[i] = d_in[i];
    S.init = true;
  }
  if (!S.ok) return;

  ChainArgs ca;
  ca.mem0 = (const bf16*)d_in[10]; ca.Mg = (uint32_t*)S.pM; ca.Sg = (float4*)S.pS; ca.flag = (uint32_t*)S.pF; ca.dbg = (uint32_t*)S.pD;
  {
    cudaLaunchConfig_t cfg = {};
    cfg.gridDim = dim3(112); cfg.blockDim = dim3(CHAIN_THREADS); cfg.dynamicSmemBytes = SMEM_CHAIN; cfg.stream = st;
    cudaLaunchAttribute at[2];
    at[0].id = cudaLaunchAttributeLaunchCompletionEvent; at[0].val.launchCompletionEvent.event = S.ev_start; at[0].val.launchCompletionEvent.flags = 0;
    at[1].id = cudaLaunchAttributeClusterDimension; at[1].val.clusterDim.x = 16; at[1].val.clusterDim.y = 1; at[1].val.clusterDim.z = 1;
    cfg.attrs = at; cfg.numAttrs = S.use_cluster ? 2 : 1;
    if (S.use_cluster) cudaLaunchKernelEx(&cfg, chain_kernel<true>, S.tx, S.tq, S.tk, S.tv, S.to, S.tka, S.tya, S.tx3, ca);
    else cudaLaunchKernelEx(&cfg, chain_kernel<false>, S.tx, S.tq, S.tk, S.tv, S.to, S.tka, S.tya, S.tx3, ca);
  }
  cudaStreamWaitEvent(S.side, S.ev_start, 0);
  SsmArgs sa;
  sa.lam_re = (const bf16*)d_in[1]; sa.lam_im = (const bf16*)d_in[2]; sa.log_dt = (const bf16*)d_in[7]; sa.dskip = (const bf16*)d_in[8];
  sa.x = (const bf16*)d_in[0]; sa.gate_w = (const bf16*)d_in[16];
  sa.hloc = (float*)S.pH; sa.hend = (float2*)S.pE; sa.omg = (float*)S.pO; sa.out = (float*)d_out;
  ssm1_kernel<<<dim3(7, 16), 160, S1_SMEM, S.side>>>(S.tbre, S.tbim, S.txp, sa);
  ssm2_kernel<<<32, 288, S2_SMEM, S.side>>>(S.tcre, S.tcim, sa);
  AttnArgs aa;
  aa.flag = (uint32_t*)S.pF; aa.ticket = (uint32_t*)S.pF + NSEG; aa.omg = (const float*)S.pO; aa.out = (float*)d_out;
  attn_kernel<<<S.n_free, 384, AT_SMEM, S.side>>>(S.tx3, S.tk3, S.ty3, aa);
  cudaEventRecord(S.ev_join, S.side);
  cudaStreamWaitEvent(st, S.ev_join, 0);
}
```

```cpp
#include <cuda_runtime.h>
#include <cuda_bf16.h>
#include <cuda.h>
#include <stdint.h>

typedef __nv_bfloat16 bf16;

namespace {

constexpr int NH = 16, DM = 448, DH = 256, SEQ = 2048, SEG = 32, NSEG = 64, NJ = 7, NMEM = 8, LKEY = 40;
constexpr int SPIN_LIMIT = 1 << 22;

#define KT_START(k) do {} while (0)
#define KT_END(k) do {} while (0)

__device__ __forceinline__ uint32_t smem_u32(const void* p) { return (uint32_t)__cvta_generic_to_shared(p); }
__device__ __forceinline__ void mbar_init(uint32_t a, uint32_t c) { asm volatile("mbarrier.init.shared.b64 [%0], %1;" ::"r"(a), "r"(c)); }
__device__ __forceinline__ void mbar_arrive(uint32_t a) { asm volatile("mbarrier.arrive.shared.b64 _, [%0];" ::"r"(a) : "memory"); }
__device__ __forceinline__ void mbar_expect_tx(uint32_t a, uint32_t b) { asm volatile("mbarrier.arrive.expect_tx.shared.b64 _, [%0], %1;" ::"r"(a), "r"(b) : "memory"); }
__device__ __forceinline__ bool mbar_try(uint32_t a, uint32_t parity) {
  uint32_t r;
  asm volatile("{\n.reg .pred p;\nmbarrier.try_wait.parity.shared.b64 p, [%1], %2;\nselp.u32 %0, 1, 0, p;\n}\n" : "=r"(r) : "r"(a), "r"(parity) : "memory");
  return r;
}
__device__ __forceinline__ bool mbar_try_cluster(uint32_t a, uint32_t parity) {
  uint32_t r;
  asm volatile("{\n.reg .pred p;\nmbarrier.try_wait.parity.acquire.cluster.shared.b64 p, [%1], %2;\nselp.u32 %0, 1, 0, p;\n}\n" : "=r"(r) : "r"(a), "r"(parity) : "memory");
  return r;
}
__device__ __forceinline__ bool mbar_test(uint32_t a, uint32_t parity) {
  uint32_t r;
  asm volatile("{\n.reg .pred p;\nmbarrier.test_wait.parity.shared.b64 p, [%1], %2;\nselp.u32 %0, 1, 0, p;\n}\n" : "=r"(r) : "r"(a), "r"(parity) : "memory");
  return r;
}
__device__ __forceinline__ void mbar_wait(uint32_t a, uint32_t parity) {
  int it = 0;
  while (!mbar_try(a, parity)) { if (++it > SPIN_LIMIT) break; }
}
__device__ __forceinline__ void mbar_wait_cluster(uint32_t a, uint32_t parity) {
  int it = 0;
  while (!mbar_try_cluster(a, parity)) { if (++it > SPIN_LIMIT) break; }
}
__device__ __forceinline__ uint32_t mapa(uint32_t a, uint32_t r) { uint32_t d; asm volatile("mapa.shared::cluster.u32 %0, %1, %2;" : "=r"(d) : "r"(a), "r"(r)); return d; }
__device__ __forceinline__ void cluster_sync_all() { asm volatile("barrier.cluster.arrive.aligned;\nbarrier.cluster.wait.aligned;" ::: "memory"); }
__device__ __forceinline__ void named_bar(int id, int n) { asm volatile("bar.sync %0, %1;" ::"r"(id), "r"(n) : "memory"); }
__device__ __forceinline__ void fence_async_smem() { asm volatile("fence.proxy.async.shared::cta;" ::: "memory"); }
__device__ __forceinline__ void fence_async_all() { asm volatile("fence.proxy.async;" ::: "memory"); }

__device__ __forceinline__ uint4 ld_vol_v4(const void* p) {
  uint4 v;
  asm volatile("ld.volatile.global.v4.u32 {%0,%1,%2,%3}, [%4];" : "=r"(v.x), "=r"(v.y), "=r"(v.z), "=r"(v.w) : "l"(p) : "memory");
  return v;
}
__device__ __forceinline__ uint32_t ld_acquire(const void* p) { uint32_t v; asm volatile("ld.acquire.gpu.global.u32 %0, [%1];" : "=r"(v) : "l"(p) : "memory"); return v; }
__device__ __forceinline__ void st_relaxed(void* p, uint32_t v) { asm volatile("st.relaxed.gpu.global.u32 [%0], %1;" ::"l"(p), "r"(v) : "memory"); }
__device__ __forceinline__ void red_v4(void* p, float a, float b, float c, float d) {
  asm volatile("red.relaxed.gpu.global.add.v4.f32 [%0], {%1,%2,%3,%4};" ::"l"(p), "f"(a), "f"(b), "f"(c), "f"(d) : "memory");
}
__device__ __forceinline__ void red_v2(void* p, float a, float b) {
  asm volatile("red.relaxed.gpu.global.add.v2.f32 [%0], {%1,%2};" ::"l"(p), "f"(a), "f"(b) : "memory");
}
__device__ __forceinline__ void red_u32(void* p, uint32_t v) { asm volatile("red.relaxed.gpu.global.add.u32 [%0], %1;" ::"l"(p), "r"(v) : "memory"); }
__device__ __forceinline__ void st_async_v4(uint32_t addr, float a, float b, float c, float d, uint32_t mbar) {
  asm volatile("st.async.shared::cluster.mbarrier::complete_tx::bytes.v4.f32 [%0], {%1,%2,%3,%4}, [%5];" ::"r"(addr), "f"(a), "f"(b), "f"(c), "f"(d), "r"(mbar) : "memory");
}

__device__ __forceinline__ void tma_load_2d(uint32_t dst, const CUtensorMap* tm, int c0, int c1, uint32_t mbar) {
  asm volatile("cp.async.bulk.tensor.2d.shared::cluster.global.mbarrier::complete_tx::bytes [%0], [%1, {%3, %4}], [%2];" ::"r"(dst), "l"(tm), "r"(mbar), "r"(c0), "r"(c1) : "memory");
}
__device__ __forceinline__ void tma_load_2d_mc(uint32_t dst, const CUtensorMap* tm, int c0, int c1, uint32_t mbar, uint16_t mask) {
  asm volatile("cp.async.bulk.tensor.2d.shared::cluster.global.mbarrier::complete_tx::bytes.multicast::cluster [%0], [%1, {%3, %4}], [%2], %5;" ::"r"(dst), "l"(tm), "r"(mbar), "r"(c0), "r"(c1), "h"(mask) : "memory");
}
__device__ __forceinline__ void tma_load_3d(uint32_t dst, const CUtensorMap* tm, int c0, int c1, int c2, uint32_t mbar) {
  asm volatile("cp.async.bulk.tensor.3d.shared::cluster.global.mbarrier::complete_tx::bytes [%0], [%1, {%3, %4, %5}], [%2];" ::"r"(dst), "l"(tm), "r"(mbar), "r"(c0), "r"(c1), "r"(c2) : "memory");
}
__device__ __forceinline__ void tma_load_4d(uint32_t dst, const CUtensorMap* tm, int c0, int c1, int c2, int c3, uint32_t mbar) {
  asm volatile("cp.async.bulk.tensor.4d.shared::cluster.global.mbarrier::complete_tx::bytes [%0], [%1, {%3, %4, %5, %6}], [%2];" ::"r"(dst), "l"(tm), "r"(mbar), "r"(c0), "r"(c1), "r"(c2), "r"(c3) : "memory");
}
__device__ __forceinline__ void tma_store_2d(const CUtensorMap* tm, int c0, int c1, uint32_t src) {
  asm volatile("cp.async.bulk.tensor.2d.global.shared::cta.bulk_group [%0, {%2, %3}], [%1];" ::"l"(tm), "r"(src), "r"(c0), "r"(c1) : "memory");
}
__device__ __forceinline__ void bulk_load(uint32_t dst, const void* src, uint32_t bytes, uint32_t mbar) {
  asm volatile("cp.async.bulk.shared::cluster.global.mbarrier::complete_tx::bytes [%0], [%1], %2, [%3];" ::"r"(dst), "l"(src), "r"(bytes), "r"(mbar) : "memory");
}
__device__ __forceinline__ void bulk_commit() { asm volatile("cp.async.bulk.commit_group;" ::: "memory"); }
template <int N> __device__ __forceinline__ void bulk_wait_read() { asm volatile("cp.async.bulk.wait_group.read %0;" ::"n"(N) : "memory"); }
template <int N> __device__ __forceinline__ void bulk_wait() { asm volatile("cp.async.bulk.wait_group %0;" ::"n"(N) : "memory"); }

__device__ __forceinline__ void wg_fence() { asm volatile("wgmma.fence.sync.aligned;" ::: "memory"); }
__device__ __forceinline__ void wg_commit() { asm volatile("wgmma.commit_group.sync.aligned;" ::: "memory"); }
template <int N> __device__ __forceinline__ void wg_wait() { asm volatile("wgmma.wait_group.sync.aligned %0;" ::"n"(N) : "memory"); }

__device__ __forceinline__ uint64_t desc_sw128(uint32_t addr) {
  return ((uint64_t)((addr & 0x3FFFF) >> 4)) | ((uint64_t)1 << 16) | ((uint64_t)(1024 >> 4) << 32) | ((uint64_t)1 << 62);
}

__device__ __forceinline__ uint32_t pack_bf16(float lo, float hi) {
  uint32_t r;
  asm("cvt.rn.bf16x2.f32 %0, %1, %2;" : "=r"(r) : "f"(hi), "f"(lo));
  return r;
}
__device__ __forceinline__ void mma16816(float* d, uint32_t a0, uint32_t a1, uint32_t a2, uint32_t a3, uint32_t b0, uint32_t b1) {
  asm volatile("mma.sync.aligned.m16n8k16.row.col.f32.bf16.bf16.f32 {%0,%1,%2,%3}, {%4,%5,%6,%7}, {%8,%9}, {%0,%1,%2,%3};"
               : "+f"(d[0]), "+f"(d[1]), "+f"(d[2]), "+f"(d[3]) : "r"(a0), "r"(a1), "r"(a2), "r"(a3), "r"(b0), "r"(b1));
}
__device__ __forceinline__ void mma1688(float* d, uint32_t a0, uint32_t a1, uint32_t b0) {
  asm volatile("mma.sync.aligned.m16n8k8.row.col.f32.bf16.bf16.f32 {%0,%1,%2,%3}, {%4,%5}, {%6}, {%0,%1,%2,%3};"
               : "+f"(d[0]), "+f"(d[1]), "+f"(d[2]), "+f"(d[3]) : "r"(a0), "r"(a1), "r"(b0));
}
__device__ __forceinline__ void ldsm_x4(uint32_t* r, uint32_t addr) {
  asm volatile("ldmatrix.sync.aligned.m8n8.x4.shared.b16 {%0,%1,%2,%3}, [%4];" : "=r"(r[0]), "=r"(r[1]), "=r"(r[2]), "=r"(r[3]) : "r"(addr) : "memory");
}
__device__ __forceinline__ void ldsm_x4_t(uint32_t* r, uint32_t addr) {
  asm volatile("ldmatrix.sync.aligned.m8n8.x4.trans.shared.b16 {%0,%1,%2,%3}, [%4];" : "=r"(r[0]), "=r"(r[1]), "=r"(r[2]), "=r"(r[3]) : "r"(addr) : "memory");
}
__device__ __forceinline__ void ldsm_x2_t(uint32_t* r, uint32_t addr) {
  asm volatile("ldmatrix.sync.aligned.m8n8.x2.trans.shared.b16 {%0,%1}, [%2];" : "=r"(r[0]), "=r"(r[1]) : "r"(addr) : "memory");
}
__device__ __forceinline__ void stsm_x4_t(uint32_t addr, uint32_t r0, uint32_t r1, uint32_t r2, uint32_t r3) {
  asm volatile("stmatrix.sync.aligned.m8n8.x4.trans.shared.b16 [%0], {%1,%2,%3,%4};" ::"r"(addr), "r"(r0), "r"(r1), "r"(r2), "r"(r3) : "memory");
}
__device__ __forceinline__ uint32_t movm_t(uint32_t a) { uint32_t d; asm volatile("movmatrix.sync.aligned.m8n8.trans.b16 %0, %1;" : "=r"(d) : "r"(a)); return d; }
__device__ __forceinline__ float ex2(float x) { float y; asm("ex2.approx.ftz.f32 %0, %1;" : "=f"(y) : "f"(x)); return y; }

__device__ __forceinline__ void wgmma_ss_n112(float* d, uint64_t descA, uint64_t descB, int scaleD) {
  asm volatile("{\n.reg .pred p;\nsetp.ne.b32 p, %58, 0;\n"
    "wgmma.mma_async.sync.aligned.m64n112k16.f32.bf16.bf16 {%0,%1,%2,%3,%4,%5,%6,%7,%8,%9,%10,%11,%12,%13,%14,%15,%16,%17,%18,%19,%20,%21,%22,%23,%24,%25,%26,%27,%28,%29,%30,%31,%32,%33,%34,%35,%36,%37,%38,%39,%40,%41,%42,%43,%44,%45,%46,%47,%48,%49,%50,%51,%52,%53,%54,%55}, %56, %57, p, 1, 1, 0, 0;\n}\n"
    : "+f"(d[0]),"+f"(d[1]),"+f"(d[2]),"+f"(d[3]),"+f"(d[4]),"+f"(d[5]),"+f"(d[6]),"+f"(d[7]),"+f"(d[8]),"+f"(d[9]),"+f"(d[10]),"+f"(d[11]),"+f"(d[12]),"+f"(d[13]),"+f"(d[14]),"+f"(d[15]),"+f"(d[16]),"+f"(d[17]),"+f"(d[18]),"+f"(d[19]),"+f"(d[20]),"+f"(d[21]),"+f"(d[22]),"+f"(d[23]),"+f"(d[24]),"+f"(d[25]),"+f"(d[26]),"+f"(d[27]),"+f"(d[28]),"+f"(d[29]),"+f"(d[30]),"+f"(d[31]),"+f"(d[32]),"+f"(d[33]),"+f"(d[34]),"+f"(d[35]),"+f"(d[36]),"+f"(d[37]),"+f"(d[38]),"+f"(d[39]),"+f"(d[40]),"+f"(d[41]),"+f"(d[42]),"+f"(d[43]),"+f"(d[44]),"+f"(d[45]),"+f"(d[46]),"+f"(d[47]),"+f"(d[48]),"+f"(d[49]),"+f"(d[50]),"+f"(d[51]),"+f"(d[52]),"+f"(d[53]),"+f"(d[54]),"+f"(d[55])
    : "l"(descA), "l"(descB), "r"(scaleD));
}
__device__ __forceinline__ void wgmma_ss_n112_ta(float* d, uint64_t descA, uint64_t descB, int scaleD) {
  asm volatile("{\n.reg .pred p;\nsetp.ne.b32 p, %58, 0;\n"
    "wgmma.mma_async.sync.aligned.m64n112k16.f32.bf16.bf16 {%0,%1,%2,%3,%4,%5,%6,%7,%8,%9,%10,%11,%12,%13,%14,%15,%16,%17,%18,%19,%20,%21,%22,%23,%24,%25,%26,%27,%28,%29,%30,%31,%32,%33,%34,%35,%36,%37,%38,%39,%40,%41,%42,%43,%44,%45,%46,%47,%48,%49,%50,%51,%52,%53,%54,%55}, %56, %57, p, 1, 1, 1, 0;\n}\n"
    : "+f"(d[0]),"+f"(d[1]),"+f"(d[2]),"+f"(d[3]),"+f"(d[4]),"+f"(d[5]),"+f"(d[6]),"+f"(d[7]),"+f"(d[8]),"+f"(d[9]),"+f"(d[10]),"+f"(d[11]),"+f"(d[12]),"+f"(d[13]),"+f"(d[14]),"+f"(d[15]),"+f"(d[16]),"+f"(d[17]),"+f"(d[18]),"+f"(d[19]),"+f"(d[20]),"+f"(d[21]),"+f"(d[22]),"+f"(d[23]),"+f"(d[24]),"+f"(d[25]),"+f"(d[26]),"+f"(d[27]),"+f"(d[28]),"+f"(d[29]),"+f"(d[30]),"+f"(d[31]),"+f"(d[32]),"+f"(d[33]),"+f"(d[34]),"+f"(d[35]),"+f"(d[36]),"+f"(d[37]),"+f"(d[38]),"+f"(d[39]),"+f"(d[40]),"+f"(d[41]),"+f"(d[42]),"+f"(d[43]),"+f"(d[44]),"+f"(d[45]),"+f"(d[46]),"+f"(d[47]),"+f"(d[48]),"+f"(d[49]),"+f"(d[50]),"+f"(d[51]),"+f"(d[52]),"+f"(d[53]),"+f"(d[54]),"+f"(d[55])
    : "l"(descA), "l"(descB), "r"(scaleD));
}
__device__ __forceinline__ void wgmma_rs_n32(float* d, const uint32_t* a, uint64_t descB, int scaleD) {
  asm volatile("{\n.reg .pred p;\nsetp.ne.b32 p, %21, 0;\n"
    "wgmma.mma_async.sync.aligned.m64n32k16.f32.bf16.bf16 {%0,%1,%2,%3,%4,%5,%6,%7,%8,%9,%10,%11,%12,%13,%14,%15}, {%16,%17,%18,%19}, %20, p, 1, 1, 0;\n}\n"
    : "+f"(d[0]),"+f"(d[1]),"+f"(d[2]),"+f"(d[3]),"+f"(d[4]),"+f"(d[5]),"+f"(d[6]),"+f"(d[7]),"+f"(d[8]),"+f"(d[9]),"+f"(d[10]),"+f"(d[11]),"+f"(d[12]),"+f"(d[13]),"+f"(d[14]),"+f"(d[15])
    : "r"(a[0]), "r"(a[1]), "r"(a[2]), "r"(a[3]), "l"(descB), "r"(scaleD));
}
__device__ __forceinline__ void wgmma_ss_n128(float* d, uint64_t descA, uint64_t descB, int scaleD) {
  asm volatile("{\n.reg .pred p;\nsetp.ne.b32 p, %66, 0;\n"
    "wgmma.mma_async.sync.aligned.m64n128k16.f32.bf16.bf16 {%0,%1,%2,%3,%4,%5,%6,%7,%8,%9,%10,%11,%12,%13,%14,%15,%16,%17,%18,%19,%20,%21,%22,%23,%24,%25,%26,%27,%28,%29,%30,%31,%32,%33,%34,%35,%36,%37,%38,%39,%40,%41,%42,%43,%44,%45,%46,%47,%48,%49,%50,%51,%52,%53,%54,%55,%56,%57,%58,%59,%60,%61,%62,%63}, %64, %65, p, 1, 1, 0, 0;\n}\n"
    : "+f"(d[0]),"+f"(d[1]),"+f"(d[2]),"+f"(d[3]),"+f"(d[4]),"+f"(d[5]),"+f"(d[6]),"+f"(d[7]),"+f"(d[8]),"+f"(d[9]),"+f"(d[10]),"+f"(d[11]),"+f"(d[12]),"+f"(d[13]),"+f"(d[14]),"+f"(d[15]),"+f"(d[16]),"+f"(d[17]),"+f"(d[18]),"+f"(d[19]),"+f"(d[20]),"+f"(d[21]),"+f"(d[22]),"+f"(d[23]),"+f"(d[24]),"+f"(d[25]),"+f"(d[26]),"+f"(d[27]),"+f"(d[28]),"+f"(d[29]),"+f"(d[30]),"+f"(d[31]),"+f"(d[32]),"+f"(d[33]),"+f"(d[34]),"+f"(d[35]),"+f"(d[36]),"+f"(d[37]),"+f"(d[38]),"+f"(d[39]),"+f"(d[40]),"+f"(d[41]),"+f"(d[42]),"+f"(d[43]),"+f"(d[44]),"+f"(d[45]),"+f"(d[46]),"+f"(d[47]),"+f"(d[48]),"+f"(d[49]),"+f"(d[50]),"+f"(d[51]),"+f"(d[52]),"+f"(d[53]),"+f"(d[54]),"+f"(d[55]),"+f"(d[56]),"+f"(d[57]),"+f"(d[58]),"+f"(d[59]),"+f"(d[60]),"+f"(d[61]),"+f"(d[62]),"+f"(d[63])
    : "l"(descA), "l"(descB), "r"(scaleD));
}
__device__ __forceinline__ void wgmma_ss_n40(float* d, uint64_t descA, uint64_t descB, int scaleD) {
  asm volatile("{\n.reg .pred p;\nsetp.ne.b32 p, %22, 0;\n"
    "wgmma.mma_async.sync.aligned.m64n40k16.f32.bf16.bf16 {%0,%1,%2,%3,%4,%5,%6,%7,%8,%9,%10,%11,%12,%13,%14,%15,%16,%17,%18,%19}, %20, %21, p, 1, 1, 0, 0;\n}\n"
    : "+f"(d[0]),"+f"(d[1]),"+f"(d[2]),"+f"(d[3]),"+f"(d[4]),"+f"(d[5]),"+f"(d[6]),"+f"(d[7]),"+f"(d[8]),"+f"(d[9]),"+f"(d[10]),"+f"(d[11]),"+f"(d[12]),"+f"(d[13]),"+f"(d[14]),"+f"(d[15]),"+f"(d[16]),"+f"(d[17]),"+f"(d[18]),"+f"(d[19])
    : "l"(descA), "l"(descB), "r"(scaleD));
}
__device__ __forceinline__ void wgmma_ss_n32_ta(float* d, uint64_t descA, uint64_t descB, int scaleD) {
  asm volatile("{\n.reg .pred p;\nsetp.ne.b32 p, %18, 0;\n"
    "wgmma.mma_async.sync.aligned.m64n32k16.f32.bf16.bf16 {%0,%1,%2,%3,%4,%5,%6,%7,%8,%9,%10,%11,%12,%13,%14,%15}, %16, %17, p, 1, 1, 1, 0;\n}\n"
    : "+f"(d[0]),"+f"(d[1]),"+f"(d[2]),"+f"(d[3]),"+f"(d[4]),"+f"(d[5]),"+f"(d[6]),"+f"(d[7]),"+f"(d[8]),"+f"(d[9]),"+f"(d[10]),"+f"(d[11]),"+f"(d[12]),"+f"(d[13]),"+f"(d[14]),"+f"(d[15])
    : "l"(descA), "l"(descB), "r"(scaleD));
}
struct ChainArgs {
  const bf16* mem0;
  uint32_t* Mg;
  float4* Sg;
  uint32_t* flag;
  uint32_t* dbg;
};

constexpr int XT_BYTES = 28672;
constexpr int STG_BYTES = 5120;
constexpr int OFF_A = 0, OFF_B = 65536, OFF_C = OFF_B + 3 * XT_BYTES, OFF_M = OFF_C + 2 * XT_BYTES, OFF_P = OFF_M + 2 * 7168,
              OFF_SX = OFF_P + 4096, OFF_SM = OFF_SX + 2048, OFF_SW = OFF_SM + 512, OFF_BAR = OFF_SW + 1024, OFF_DBG = OFF_B + 2 * XT_BYTES + 3 * 7168, SMEM_CHAIN = OFF_BAR + 512;
enum { B_PA = 0, B_PE = 1, B_XF = 4, B_MB = 9, B_SX = 11, B_SM = 13, B_PB = 15, B_KR = 17, B_ST = 21, B_PF = 29, B_RD = 45, B_MF = 47, B_EM = 51, B_SB = 55, B_PE5 = 56, B_NUM = 61 };
#define MD0 250
#define MDELTA 900
#define SSTART 850
#define SXSTART 700
#define SSTAG 130
constexpr float L2E = 1.4426950408889634f;
constexpr int CHAIN_THREADS = 512;
#define TOKK 28

__device__ __forceinline__ uint32_t xstage_off(int st) { return st < 2 ? OFF_C + st * XT_BYTES : OFF_B + (st - 2) * XT_BYTES; }
__device__ __forceinline__ uint32_t mslot_off(int k) { return k < 3 ? OFF_B + 2 * XT_BYTES + k * 7168 : OFF_M; }
constexpr int OFF_VAR = OFF_BAR + 496;

__device__ __forceinline__ bool slot_has_sentinel(const uint8_t* p, int lane) {
  bool bad = false;
#pragma unroll 2
  for (int i = 0; i < 14; i++) { const uint4 v = *reinterpret_cast<const uint4*>(p + (32 * i + lane) * 16); bad |= (v.x == ~0u) | (v.y == ~0u) | (v.z == ~0u) | (v.w == ~0u); }
  return __any_sync(~0u, bad);
}
__device__ __forceinline__ uint32_t clk32() { uint32_t c; asm volatile("mov.u32 %0, %%clock;" : "=r"(c)); return c; }
#define DBG(slot) do {} while (0)

#define PDBG(i) do {} while (0)

template <bool CL>
__device__ __forceinline__ void issue_x_load(uint32_t sb, const CUtensorMap* tm_x, const CUtensorMap* tm_x3, int seg, int rank) {
  const int st = seg & 3;
  const uint32_t bar = sb + OFF_BAR + (B_XF + st) * 8;
  const uint32_t dst = sb + xstage_off(st);
  mbar_expect_tx(bar, XT_BYTES);
  if (CL) {
    if (rank < NJ) tma_load_2d_mc(dst + rank * 4096, tm_x, rank * 64, seg * SEG, bar, (uint16_t)0xFFFF);
  } else {
    tma_load_3d(dst, tm_x3, 0, seg * SEG, 0, bar);
  }
}

template <int WG>
__device__ __forceinline__ void tile_prologue(uint32_t* W, uint32_t sb) {
  const uint32_t bar = sb + OFF_BAR;
  const int lane = threadIdx.x & 31;
  float acc[112];
  mbar_wait(bar + B_PA * 8, 0);
#pragma unroll
  for (int half = 0; half < 2; half++) {
#pragma unroll
    for (int ec = 0; ec < 4; ec++) {
      const int i = half * 8 + ec * 2 + WG;
      const int st = i % 5;
      mbar_wait(bar + (B_PF + i) * 8, 0);
      const uint32_t bb = sb + OFF_B + st * XT_BYTES;
      wg_fence();
#pragma unroll
      for (int kk = 0; kk < 4; kk++) {
        if (WG == 0) {
          wgmma_ss_n112(acc, desc_sw128(sb + OFF_A + ec * 8192 + kk * 32), desc_sw128(bb + kk * 32), (ec | kk) != 0);
          wgmma_ss_n112(acc + 56, desc_sw128(sb + OFF_A + ec * 8192 + kk * 32), desc_sw128(bb + 14336 + kk * 32), (ec | kk) != 0);
        } else {
          wgmma_ss_n112_ta(acc, desc_sw128(sb + OFF_A + 32768 + (ec * 64 + kk * 16) * 128), desc_sw128(bb + kk * 32), (ec | kk) != 0);
          wgmma_ss_n112_ta(acc + 56, desc_sw128(sb + OFF_A + 32768 + (ec * 64 + kk * 16) * 128), desc_sw128(bb + 14336 + kk * 32), (ec | kk) != 0);
        }
      }
      wg_commit();
      wg_wait<0>();
      if (lane == 0) mbar_arrive(bar + (B_PE5 + st) * 8);
    }
    const float sc = WG == 0 ? 0.0625f : 1.0f;
#pragma unroll
    for (int kk = 0; kk < 14; kk++) {
      W[half * 56 + kk * 4 + 0] = pack_bf16(acc[8 * kk + 0] * sc, acc[8 * kk + 1] * sc);
      W[half * 56 + kk * 4 + 1] = pack_bf16(acc[8 * kk + 2] * sc, acc[8 * kk + 3] * sc);
      W[half * 56 + kk * 4 + 2] = pack_bf16(acc[8 * kk + 4] * sc, acc[8 * kk + 5] * sc);
      W[half * 56 + kk * 4 + 3] = pack_bf16(acc[8 * kk + 6] * sc, acc[8 * kk + 7] * sc);
    }
  }
}

__device__ __forceinline__ void token_gemm(const uint32_t* W, uint32_t sb, int seg, uint32_t stg_base, int w, int lane) {
  const int st = seg & 3;
  mbar_wait(sb + OFF_BAR + (B_XF + st) * 8, (seg >> 2) & 1);
  const uint32_t xb = sb + xstage_off(st);
  float d[16];
  wg_fence();
#pragma unroll
  for (int kk = 0; kk < TOKK; kk++) wgmma_rs_n32(d, &W[4 * kk], desc_sw128(xb + (kk >> 2) * 4096 + (kk & 3) * 32), kk != 0);
  wg_commit();
  wg_wait<0>();
  const uint32_t stg = stg_base + (seg & 3) * STG_BYTES + 1024;
  const int r = lane & 7, mi = lane >> 3;
#pragma unroll
  for (int p = 0; p < 2; p++) {
    const int t = 8 * (2 * p + (mi >> 1)) + r;
    const int chunk = 2 * w + (mi & 1);
    const uint32_t addr = stg + t * 128 + ((chunk ^ r) << 4);
    stsm_x4_t(addr, pack_bf16(d[8 * p + 0], d[8 * p + 1]), pack_bf16(d[8 * p + 2], d[8 * p + 3]), pack_bf16(d[8 * p + 4], d[8 * p + 5]),
              pack_bf16(d[8 * p + 6], d[8 * p + 7]));
  }
}

__device__ __forceinline__ void poll_smm(uint8_t* smem, uint32_t bar, const float4* src, int s, int p, int lane) {
  volatile uint32_t* var = reinterpret_cast<volatile uint32_t*>(smem + OFF_VAR);
  { int it = 0; while (var[1] != (uint32_t)s && ++it < SPIN_LIMIT) __nanosleep(20); }
  const uint32_t tM = clk32();
  while ((int)(clk32() - tM) < SSTART + p * SSTAG) {}
  uint4 v; int it = 0; bool mine = true;
  while (true) {
    v = ld_vol_v4(src);
    if (__all_sync(~0u, __uint_as_float(v.z) == 7.f)) break;
    if (mbar_test(bar + (B_SM + (s & 1)) * 8, (s >> 1) & 1)) { mine = false; break; }
    if (++it > SPIN_LIMIT) break;
  }
  if (mine) {
    reinterpret_cast<float2*>(smem + OFF_SM + (s & 1) * 256)[lane] = make_float2(__uint_as_float(v.x), __uint_as_float(v.y));
    __syncwarp();
    if (lane == 0) { if (atomicExch(reinterpret_cast<uint32_t*>(smem + OFF_VAR), (uint32_t)(s + 1)) != (uint32_t)(s + 1)) mbar_arrive(bar + (B_SM + (s & 1)) * 8); }
  }
}

template <bool CL>
__global__ void __launch_bounds__(CHAIN_THREADS, 1)
chain_kernel(const __grid_constant__ CUtensorMap tm_x, const __grid_constant__ CUtensorMap tm_wq, const __grid_constant__ CUtensorMap tm_wk,
             const __grid_constant__ CUtensorMap tm_wv, const __grid_constant__ CUtensorMap tm_wo, const __grid_constant__ CUtensorMap tm_k,
             const __grid_constant__ CUtensorMap tm_y, const __grid_constant__ CUtensorMap tm_x3, ChainArgs args) {
  extern __shared__ __align__(1024) uint8_t smem[];
  const uint32_t sb = smem_u32(smem);
  const int tid = threadIdx.x, warp = tid >> 5, lane = tid & 31;
  const int j = blockIdx.x >> 4, h = blockIdx.x & 15;
  const uint32_t bar = sb + OFF_BAR;
  const int g = lane >> 2, q = lane & 3;
  KT_START(0);

  if (tid == 0) {
    mbar_init(bar + B_PA * 8, 1);
    for (int i = 0; i < 5; i++) mbar_init(bar + (B_PE5 + i) * 8, 4);
    for (int i = 0; i < 16; i++) mbar_init(bar + (B_PF + i) * 8, 1);
    for (int i = 0; i < 5; i++) mbar_init(bar + (B_XF + i) * 8, 1);
    for (int i = 0; i < 2; i++) {
      mbar_init(bar + (B_SX + i) * 8, 4); mbar_init(bar + (B_SM + i) * 8, 1); mbar_init(bar + (B_PB + i) * 8, 1); mbar_init(bar + (B_RD + i) * 8, 1);
    }
    for (int i = 0; i < 4; i++) { mbar_init(bar + (B_KR + i) * 8, 4); mbar_init(bar + (B_MF + i) * 8, 1); mbar_init(bar + (B_EM + i) * 8, 4); }
    mbar_init(bar + B_SB * 8, 1);
    for (int i = 0; i < 8; i++) mbar_init(bar + (B_ST + i) * 8, 4);
    asm volatile("fence.mbarrier_init.release.cluster;" ::: "memory");
  }
  __syncthreads();
  if (CL) cluster_sync_all();
  asm volatile("griddepcontrol.launch_dependents;" ::: "memory");
  PDBG(0);

  const int wgi = __shfl_sync(0xffffffffu, tid >> 7, 0);
  if (wgi < 2) {
    asm volatile("setmaxnreg.inc.sync.aligned.u32 200;");
    const int wg = wgi, w = warp & 3;
    uint32_t W[112];
    mbar_wait(bar + B_PA * 8, 0);
    PDBG(1);
    mbar_wait(bar + B_PF * 8, 0);
    PDBG(2);
    if (wg == 0) tile_prologue<0>(W, sb); else tile_prologue<1>(W, sb);
    PDBG(3);
    named_bar(0, CHAIN_THREADS);
    PDBG(4);
    PDBG(5);

    const uint32_t stg_base = sb + OFF_A + wg * 4 * STG_BYTES;
    token_gemm(W, sb, 0, stg_base, w, lane);
    PDBG(6);
    PDBG(7);
    __syncwarp();
    if (wg == 0 && lane == 0) mbar_arrive(bar + (B_KR + 0) * 8);

    if (wg == 0) {
      for (int s = 0; s < NSEG; s++) {
        float d0, d1, d2, d3;
        uint32_t ma[2];
        volatile uint32_t* var = reinterpret_cast<volatile uint32_t*>(smem + OFF_VAR);
        mbar_wait(bar + B_SB * 8, s & 1);
        uint32_t n = var[3];
        const uint32_t n_first = n;
        while (true) {
          const int slot = n & 3;
          mbar_wait(bar + (B_MF + slot) * 8, (n >> 2) & 1);
          if (tid == 0) DBG(0);
          const uint32_t ms = sb + mslot_off(slot);
          float a4[4][4];
#pragma unroll
          for (int i = 0; i < 4; i++) { a4[i][0] = a4[i][1] = a4[i][2] = a4[i][3] = 0.f; }
          uint32_t b[14][4];
#pragma unroll
          for (int i = 0; i < 14; i++) ldsm_x4_t(b[i], ms + (32 * i + lane) * 16);
          ldsm_x2_t(ma, ms + (64 * j + 16 * w + (lane & 15)) * 16);
#pragma unroll
          for (int i = 0; i < 14; i++) {
            mma16816(a4[(2 * i) & 3], W[8 * i + 0], W[8 * i + 1], W[8 * i + 2], W[8 * i + 3], b[i][0], b[i][1]);
            mma16816(a4[(2 * i + 1) & 3], W[8 * i + 4], W[8 * i + 5], W[8 * i + 6], W[8 * i + 7], b[i][2], b[i][3]);
          }
          d0 = (a4[0][0] + a4[1][0]) + (a4[2][0] + a4[3][0]); d1 = (a4[0][1] + a4[1][1]) + (a4[2][1] + a4[3][1]);
          d2 = (a4[0][2] + a4[1][2]) + (a4[2][2] + a4[3][2]); d3 = (a4[0][3] + a4[1][3]) + (a4[2][3] + a4[3][3]);
          if (!__any_sync(~0u, (d0 != d0) | (d1 != d1))) break;
          if (!slot_has_sentinel(smem + mslot_off(slot), lane)) break;
          if (n - n_first > (uint32_t)SPIN_LIMIT) break;
          if (lane == 0) mbar_arrive(bar + (B_EM + slot) * 8);
          n++;
        }
        if (tid == 0) { var[2] = n; var[1] = s; reinterpret_cast<uint32_t*>(smem + OFF_DBG)[s * 16 + 14] = n - n_first; }
        asm volatile("bar.arrive 5, 256;" ::: "memory");
        if (tid == 0) { asm volatile("" :: "f"(d0), "f"(d3)); DBG(8); }
        const uint32_t kb0 = movm_t(pack_bf16(d0, d1)), kb1 = movm_t(pack_bf16(d2, d3));
        if (s < NSEG - 1) {
          float c[4] = {0.f, 0.f, 0.f, 0.f};
          mma16816(c, ma[0], 0u, ma[1], 0u, kb0, kb1);
          float2* sw = reinterpret_cast<float2*>(smem + OFF_SW);
          sw[w * 32 + lane] = make_float2(c[0], c[1]);
          if (tid == 0) DBG(9);
          named_bar(1, 128);
          if (tid == 0) DBG(10);
          if (w == 0) {
            const float2 v0 = sw[lane], v1 = sw[32 + lane], v2 = sw[64 + lane], v3 = sw[96 + lane];
            red_v4(args.Sg + (((size_t)s * NH + h) * 5 + 4) * 32 + lane, (v0.x + v1.x) + (v2.x + v3.x), (v0.y + v1.y) + (v2.y + v3.y), 1.f, 0.f);
          }
        }
        asm volatile("bar.arrive 3, 256;" ::: "memory");
        if (tid == 0) DBG(1);
        {
          const uint32_t stg = stg_base + (s & 3) * STG_BYTES + g * 128 + q * 4;
          asm volatile("st.shared.u32 [%0], %1;" ::"r"(stg + (((2 * w) ^ g) << 4)), "r"(kb0) : "memory");
          asm volatile("st.shared.u32 [%0], %1;" ::"r"(stg + (((2 * w + 1) ^ g) << 4)), "r"(kb1) : "memory");
          fence_async_smem();
          __syncwarp();
          if (lane == 0) mbar_arrive(bar + (B_ST + (s & 3)) * 8);
        }
        if (s + 1 < NSEG) {
          token_gemm(W, sb, s + 1, stg_base, w, lane);
          __syncwarp();
          if (lane == 0) mbar_arrive(bar + (B_KR + ((s + 1) & 3)) * 8);
        }
        if (tid == 0) DBG(11);
        named_bar(1, 128);
      }
    } else {
      const int hd = w * 4 + (lane >> 3);
      uint32_t p_dst = sb + OFF_P + h * 128 + (lane & 7) * 16, p_bar = bar + B_PB * 8;
      if (CL) { p_dst = mapa(p_dst, hd); p_bar = mapa(p_bar, hd); }
      const uint32_t ONE2 = 0x3F803F80u;
      for (int s = 0; s < NSEG; s++) {
        if (s < NSEG - 1) {
          mbar_wait(bar + (B_KR + (s & 3)) * 8, (s >> 2) & 1);
          const uint32_t kst = sb + OFF_A + (s & 3) * STG_BYTES + 1024;
          uint32_t bk[2][4];
#pragma unroll
          for (int i = 0; i < 2; i++) ldsm_x4(bk[i], kst + (8 * w + (lane & 7)) * 128 + (((4 * i + (lane >> 3)) ^ (lane & 7)) << 4));
          float c[4] = {0.f, 0.f, 0.f, 0.f}, c2[4] = {0.f, 0.f, 0.f, 0.f};
          named_bar(5, 256);
          {
            const uint32_t ms = sb + mslot_off(reinterpret_cast<volatile uint32_t*>(smem + OFF_VAR)[2] & 3);
            uint32_t a[2][4];
            ldsm_x4_t(a[0], ms + (64 * j + lane) * 16);
            ldsm_x4_t(a[1], ms + (64 * j + 32 + lane) * 16);
            mma16816(c, a[0][0], 0u, a[0][1], 0u, bk[0][0], bk[0][1]);
            mma16816(c2, a[0][2], 0u, a[0][3], 0u, bk[0][2], bk[0][3]);
            mma16816(c, a[1][0], 0u, a[1][1], 0u, bk[1][0], bk[1][1]);
            mma16816(c2, a[1][2], 0u, a[1][3], 0u, bk[1][2], bk[1][3]);
            c[0] += c2[0]; c[1] += c2[1];
          }
          red_v4(args.Sg + (((size_t)s * NH + h) * 5 + w) * 32 + lane, c[0], c[1], 1.f, 0.f);
        } else named_bar(5, 256);
        named_bar(3, 256);
        const uint32_t ms = sb + mslot_off(reinterpret_cast<volatile uint32_t*>(smem + OFF_VAR)[2] & 3);
        float a4[4][4];
#pragma unroll
        for (int i = 0; i < 4; i++) { a4[i][0] = a4[i][1] = a4[i][2] = a4[i][3] = 0.f; }
        {
          uint32_t b[14][4];
#pragma unroll
          for (int i = 0; i < 14; i++) ldsm_x4_t(b[i], ms + (32 * i + lane) * 16);
#pragma unroll
          for (int i = 0; i < 14; i++) {
            mma16816(a4[(2 * i) & 3], W[8 * i + 0], W[8 * i + 1], W[8 * i + 2], W[8 * i + 3], b[i][0], b[i][1]);
            mma16816(a4[(2 * i + 1) & 3], W[8 * i + 4], W[8 * i + 5], W[8 * i + 6], W[8 * i + 7], b[i][2], b[i][3]);
          }
        }
        const uint32_t za0 = pack_bf16((a4[0][0] + a4[1][0]) + (a4[2][0] + a4[3][0]), (a4[0][1] + a4[1][1]) + (a4[2][1] + a4[3][1]));
        const uint32_t za1 = pack_bf16((a4[0][2] + a4[1][2]) + (a4[2][2] + a4[3][2]), (a4[0][3] + a4[1][3]) + (a4[2][3] + a4[3][3]));
        {
          const uint32_t stg = stg_base + (s & 3) * STG_BYTES + g * 128 + q * 4;
          asm volatile("st.shared.u32 [%0], %1;" ::"r"(stg + (((2 * w) ^ g) << 4)), "r"(movm_t(za0)) : "memory");
          asm volatile("st.shared.u32 [%0], %1;" ::"r"(stg + (((2 * w + 1) ^ g) << 4)), "r"(movm_t(za1)) : "memory");
          fence_async_smem();
          __syncwarp();
          if (lane == 0) mbar_arrive(bar + (B_ST + 4 + (s & 3)) * 8);
        }
        if (s < NSEG - 1) {
          uint32_t va[2][4];
          const uint32_t vst = stg_base + (s & 3) * STG_BYTES + 1024;
#pragma unroll
          for (int kk = 0; kk < 2; kk++) {
            const int mi = lane >> 3, r = lane & 7;
            const int t = 8 * (2 * kk + (mi >> 1)) + r;
            ldsm_x4_t(va[kk], vst + t * 128 + (((2 * w + (mi & 1)) ^ r) << 4));
          }
          mbar_wait(bar + (B_SX + (s & 1)) * 8, (s >> 1) & 1);
          const float2* sx = reinterpret_cast<const float2*>(smem + OFF_SX + (s & 1) * 1024);
          float ex[8];
#pragma unroll
          for (int nt = 0; nt < 4; nt++) { const float2 v = sx[nt * 32 + lane]; ex[2 * nt] = v.x; ex[2 * nt + 1] = v.y; }
          float mx = fmaxf(fmaxf(fmaxf(ex[0], ex[1]), fmaxf(ex[2], ex[3])), fmaxf(fmaxf(ex[4], ex[5]), fmaxf(ex[6], ex[7])));
          mx = fmaxf(mx, __shfl_xor_sync(~0u, mx, 1));
          mx = fmaxf(mx, __shfl_xor_sync(~0u, mx, 2));
#pragma unroll
          for (int k = 0; k < 8; k++) ex[k] = ex2((ex[k] - mx) * L2E);
          mbar_wait(bar + (B_SM + (s & 1)) * 8, (s >> 1) & 1);
          if (tid == 128) DBG(2);
          const float2 sm = reinterpret_cast<const float2*>(smem + OFF_SM + (s & 1) * 256)[lane];
          float mm = fmaxf(sm.x, sm.y);
          mm = fmaxf(mm, __shfl_xor_sync(~0u, mm, 1));
          mm = fmaxf(mm, __shfl_xor_sync(~0u, mm, 2));
          const float m = fmaxf(mx, mm);
          const float f = ex2((mx - m) * L2E);
          const uint32_t pm = pack_bf16(ex2((sm.x - m) * L2E), ex2((sm.y - m) * L2E));
          uint32_t bx[4];
#pragma unroll
          for (int nt = 0; nt < 4; nt++) bx[nt] = pack_bf16(ex[2 * nt] * f, ex[2 * nt + 1] * f);
          float o0[4] = {0.f, 0.f, 0.f, 0.f}, o1[4] = {0.f, 0.f, 0.f, 0.f}, o2[4] = {0.f, 0.f, 0.f, 0.f};
          float l0[4] = {0.f, 0.f, 0.f, 0.f}, l1[4] = {0.f, 0.f, 0.f, 0.f}, l2[4] = {0.f, 0.f, 0.f, 0.f};
          mma1688(o0, za0, za1, pm);
          mma1688(l0, ONE2, ONE2, pm);
          mma16816(o1, va[0][0], va[0][1], va[0][2], va[0][3], bx[0], bx[1]);
          mma16816(l1, ONE2, ONE2, ONE2, ONE2, bx[0], bx[1]);
          mma16816(o2, va[1][0], va[1][1], va[1][2], va[1][3], bx[2], bx[3]);
          mma16816(l2, ONE2, ONE2, ONE2, ONE2, bx[2], bx[3]);
          const float r0 = __fdividef(1.f, l0[0] + l1[0] + l2[0]), r1 = __fdividef(1.f, l0[1] + l1[1] + l2[1]);
          const float v0 = (o0[0] + o1[0] + o2[0]) * r0, v1 = (o0[1] + o1[1] + o2[1]) * r1;
          const float v2 = (o0[2] + o1[2] + o2[2]) * r0, v3 = (o0[3] + o1[3] + o2[3]) * r1;
          if (CL) {
            st_async_v4(p_dst + (s & 1) * 2048, v0, v1, v2, v3, p_bar + (s & 1) * 8);
          } else {
            uint4* dst = reinterpret_cast<uint4*>(args.Sg + (size_t)NSEG * NH * 5 * 32) + ((((size_t)s * NJ + j) * 16 + hd) * 16 + h) * 8 + (lane & 7);
            uint32_t u0 = ~__float_as_uint(v0), u1 = ~__float_as_uint(v1), u2 = ~__float_as_uint(v2), u3 = ~__float_as_uint(v3);
            u0 += (u0 == 0); u1 += (u1 == 0); u2 += (u2 == 0); u3 += (u3 == 0);
            asm volatile("st.relaxed.gpu.global.v4.u32 [%0], {%1,%2,%3,%4};" ::"l"(dst), "r"(u0), "r"(u1), "r"(u2), "r"(u3) : "memory");
          }
          if (tid == 128) DBG(3);
        }
        if (s + 1 < NSEG) token_gemm(W, sb, s + 1, stg_base, w, lane);
        if (tid == 128) DBG(12);
      }
    }
  } else if (wgi == 2) {
    asm volatile("setmaxnreg.dec.sync.aligned.u32 80;");
    const int aw = warp - 8, at = tid - 256;
    named_bar(0, CHAIN_THREADS);
    for (int s = 0; s < NSEG; s++) {
      volatile uint32_t* var = reinterpret_cast<volatile uint32_t*>(smem + OFF_VAR);
      if (s == 0) {
        for (int c = at; c < DM; c += 128) {
          uint32_t v[4];
#pragma unroll
          for (int i = 0; i < 4; i++) {
            uint32_t lo = reinterpret_cast<const uint16_t*>(args.mem0)[(2 * i) * DM + c], hi = reinterpret_cast<const uint16_t*>(args.mem0)[(2 * i + 1) * DM + c];
            if (lo == 0xFFFFu) lo = 0x7FFFu;
            if (hi == 0xFFFFu) hi = 0x7FFFu;
            v[i] = lo | (hi << 16);
          }
          *reinterpret_cast<uint4*>(smem + mslot_off(0) + c * 16) = make_uint4(v[0], v[1], v[2], v[3]);
        }
        named_bar(2, 128);
        if (at == 0) mbar_arrive(bar + B_MF * 8);
      }
      { int it = 0; while (var[1] != (uint32_t)s && ++it < SPIN_LIMIT) __nanosleep(20); }
      if (j == 0) {
        const float4 z4 = make_float4(0.f, 0.f, 0.f, 0.f);
        if (s >= 2) { float4* p = args.Sg + ((size_t)(s - 2) * NH + h) * 160; p[aw * 32 + lane] = z4; if (aw == 0) p[128 + lane] = z4; }
        if (s == NSEG - 1) { float4* p = args.Sg + ((size_t)(s - 1) * NH + h) * 160; p[aw * 32 + lane] = z4; if (aw == 0) p[128 + lane] = z4; }
      }
      if (at == 32) DBG(4);
      if (s == NSEG - 1) break;
      const uint32_t tM = clk32();
      {
        const float4* src = args.Sg + (((size_t)s * NH + h) * 5 + aw) * 32 + lane;
        while ((int)(clk32() - tM) < SXSTART) {}
        uint4 v; int it = 0;
        do { v = ld_vol_v4(src); } while (__uint_as_float(v.z) != 7.f && ++it < SPIN_LIMIT);
        reinterpret_cast<float2*>(smem + OFF_SX + (s & 1) * 1024)[aw * 32 + lane] = make_float2(__uint_as_float(v.x), __uint_as_float(v.y));
        __syncwarp();
        if (lane == 0) mbar_arrive(bar + (B_SX + (s & 1)) * 8);
        if (at == 0) DBG(13);
      }
    }
  } else {
    asm volatile("setmaxnreg.dec.sync.aligned.u32 32;");
    if (tid == 384) {
      reinterpret_cast<uint32_t*>(smem + OFF_VAR)[0] = 0; reinterpret_cast<uint32_t*>(smem + OFF_VAR)[1] = ~0u;
      mbar_expect_tx(bar + B_PA * 8, 65536);
#pragma unroll
      for (int ec = 0; ec < 4; ec++) tma_load_2d(sb + OFF_A + ec * 8192, &tm_wq, h * DH + ec * 64, 64 * j, bar + B_PA * 8);
      tma_load_2d(sb + OFF_A + 32768, &tm_wo, 64 * j, h * DH, bar + B_PA * 8);
      for (int i = 0; i < 16; i++) {
        const int st = i % 5, half = i >> 3, ec = (i & 7) >> 1;
        if (i >= 5) mbar_wait(bar + (B_PE5 + st) * 8, ((i / 5) - 1) & 1);
        mbar_expect_tx(bar + (B_PF + i) * 8, XT_BYTES);
        tma_load_2d(sb + OFF_B + st * XT_BYTES, (i & 1) ? &tm_wv : &tm_wk, h * DH + ec * 64, half * 224, bar + (B_PF + i) * 8);
      }
    }
    if (tid == 384) {
#pragma unroll 1
      for (int sg = 0; sg < 2; sg++) {
        mbar_wait(bar + (B_PE5 + 3 + sg) * 8, 0);
        mbar_expect_tx(bar + (B_XF + sg) * 8, XT_BYTES);
        tma_load_3d(sb + xstage_off(sg), &tm_x3, 0, sg * SEG, 0, bar + (B_XF + sg) * 8);
      }
    }
    if (warp == 13 && !(lane & 1)) {
      const int l8 = lane >> 2, v = lane & 3;
      const int c = 16 * (h >> 2) + 2 * (h & 3) + (l8 >> 2) + (v >> 1) * 8;
      for (int s = 1; s < NSEG; s++) st_relaxed(args.Mg + (size_t)s * 1792 + (64 * j + c) * 4 + (l8 & 3), 0xFFFFFFFFu);
      __threadfence();
    }
    __syncwarp();
    named_bar(0, CHAIN_THREADS);
    if (tid == 384) {
      issue_x_load<false>(sb, &tm_x, &tm_x3, 2, h);
      for (int s = 0; s < NSEG; s++) {
        mbar_wait(bar + (B_ST + (s & 3)) * 8, (s >> 2) & 1);
        tma_store_2d(&tm_k, 64 * j, (h * NSEG + s) * LKEY, sb + OFF_A + (s & 3) * STG_BYTES);
        mbar_wait(bar + (B_ST + 4 + (s & 3)) * 8, (s >> 2) & 1);
        tma_store_2d(&tm_y, 64 * j, (h * NSEG + s) * LKEY, sb + OFF_A + (4 + (s & 3)) * STG_BYTES);
        bulk_commit();
        if (s + 3 < NSEG) { if (s == 0) issue_x_load<false>(sb, &tm_x, &tm_x3, 3, h); else issue_x_load<CL>(sb, &tm_x, &tm_x3, s + 3, h); }
        bulk_wait<0>();
        fence_async_all();
        __threadfence();
        red_u32(args.flag + s, 1u);
      }
    } else if (warp == 13) {
      for (int s = 0; s < NSEG - 1; s++) {
        float acc;
        if (CL && lane == 0) mbar_expect_tx(bar + (B_PB + (s & 1)) * 8, 16 * 128);
        poll_smm(smem, bar, args.Sg + (((size_t)s * NH + h) * 5 + 4) * 32 + lane, s, 1, lane);
        if (CL) {
          mbar_wait_cluster(bar + (B_PB + (s & 1)) * 8, (s >> 1) & 1);
          if (lane == 0) DBG(5);
          const float* pin = reinterpret_cast<const float*>(smem + OFF_P + (s & 1) * 2048);
          float a0 = 0.f, a1 = 0.f, a2 = 0.f, a3 = 0.f;
#pragma unroll
          for (int k = 0; k < 16; k += 4) { a0 += pin[k * 32 + lane]; a1 += pin[(k + 1) * 32 + lane]; a2 += pin[(k + 2) * 32 + lane]; a3 += pin[(k + 3) * 32 + lane]; }
          acc = (a0 + a1) + (a2 + a3);
        } else {
          const uint32_t* src = reinterpret_cast<const uint32_t*>(args.Sg + (size_t)NSEG * NH * 5 * 32) + (((size_t)s * NJ + j) * 16 + h) * 16 * 32 + lane;
          acc = 0.f;
#pragma unroll 1
          for (int k = 0; k < 16; k += 4) {
            uint32_t v0, v1, v2, v3; int it = 0;
            do {
              asm volatile("ld.volatile.global.u32 %0, [%1];" : "=r"(v0) : "l"(src + k * 32) : "memory");
              asm volatile("ld.volatile.global.u32 %0, [%1];" : "=r"(v1) : "l"(src + k * 32 + 32) : "memory");
              asm volatile("ld.volatile.global.u32 %0, [%1];" : "=r"(v2) : "l"(src + k * 32 + 64) : "memory");
              asm volatile("ld.volatile.global.u32 %0, [%1];" : "=r"(v3) : "l"(src + k * 32 + 96) : "memory");
            } while ((v0 == 0u || v1 == 0u || v2 == 0u || v3 == 0u) && ++it < SPIN_LIMIT);
            acc += (__uint_as_float(~v0) + __uint_as_float(~v1)) + (__uint_as_float(~v2) + __uint_as_float(~v3));
            uint32_t* cl = const_cast<uint32_t*>(src) + k * 32;
            cl[0] = 0u; cl[32] = 0u; cl[64] = 0u; cl[96] = 0u;
          }
        }
        const float o = __shfl_down_sync(~0u, acc, 1);
        const uint32_t u = pack_bf16(acc, o);
        const int l8 = lane >> 2, v = lane & 3;
        const int c = 16 * (h >> 2) + 2 * (h & 3) + (l8 >> 2) + (v >> 1) * 8;
        if (!(lane & 1)) st_relaxed(args.Mg + (size_t)(s + 1) * 1792 + (64 * j + c) * 4 + (l8 & 3), u);
        if (lane == 0) { DBG(6); mbar_arrive(bar + (B_RD + (s & 1)) * 8); }
      }
    } else if (warp == 15) {
      for (int s = 0; s < NSEG - 1; s++) poll_smm(smem, bar, args.Sg + (((size_t)s * NH + h) * 5 + 4) * 32 + lane, s, 0, lane);
    } else if (tid == 448) {
      volatile uint32_t* var = reinterpret_cast<volatile uint32_t*>(smem + OFF_VAR);
      uint32_t n = 0, empar = 0;
      for (int s = 0; s < NSEG; s++) {
        if (s > 0) mbar_wait(bar + (B_RD + ((s - 1) & 1)) * 8, ((s - 1) >> 1) & 1);
        const uint32_t n0 = n;
        var[3] = n0;
        mbar_arrive(bar + B_SB * 8);
        uint32_t tnext = clk32() + MD0;
        int it = 0;
        if (s == 0) n = 1;
        while (s > 0) {
          bool done = false;
          while ((int)(clk32() - tnext) < 0) { if (var[1] == (uint32_t)s) { done = true; break; } }
          if (done || var[1] == (uint32_t)s || ++it > SPIN_LIMIT) break;
          const int slot = n & 3;
          if (n - n0 >= 4) {
            int it2 = 0;
            while (!mbar_test(bar + (B_EM + slot) * 8, (empar >> slot) & 1)) { if (var[1] == (uint32_t)s || ++it2 > SPIN_LIMIT) { done = true; break; } }
            if (done) break;
            empar ^= 1u << slot;
          }
          mbar_expect_tx(bar + (B_MF + slot) * 8, 7168);
          bulk_load(sb + mslot_off(slot), args.Mg + (size_t)s * 1792, 7168, bar + (B_MF + slot) * 8);
          n++;
          tnext += MDELTA;
        }
        { int it3 = 0; while (var[1] != (uint32_t)s && ++it3 < SPIN_LIMIT) {} }
        const uint32_t ns = var[2];
        const uint32_t waited = n - n0 > 4 ? n - n0 - 4 : 0;
        for (uint32_t a = n0 + waited; a < ns; a++) empar ^= 1u << (a & 3);
        for (uint32_t a = ns + 1; a < n; a++) mbar_wait(bar + (B_MF + (a & 3)) * 8, (a >> 2) & 1);
        reinterpret_cast<uint32_t*>(smem + OFF_DBG)[s * 16 + 15] = n - n0;
      }
    }
    __syncwarp();
  }
  named_bar(0, CHAIN_THREADS);
  KT_END(0);
  if (CL) cluster_sync_all();
}
struct SsmArgs {
  const bf16 *lam_re, *lam_im, *log_dt, *dskip, *x, *gate_w;
  float* hloc;
  float2* hend;
  float* omg;
  float* gate;
  float4* tab;
  float* out;
};

__device__ __forceinline__ float bf2f(bf16 v) { return __bfloat162float(v); }
__device__ __forceinline__ float rbf(float v) { return __bfloat162float(__float2bfloat16_rn(v)); }
__device__ __forceinline__ float2 cmul(float2 a, float2 b) { return make_float2(a.x * b.x - a.y * b.y, a.x * b.y + a.y * b.x); }
__device__ __forceinline__ float2 ssm_z(const SsmArgs& a, int ch) {
  const float dt = rbf(expf(bf2f(a.log_dt[ch])));
  return make_float2(dt * bf2f(a.lam_re[ch]), dt * bf2f(a.lam_im[ch]));
}
__device__ __forceinline__ float2 cexp_n(float2 z, float n) {
  float sn, cs;
  sincosf(z.y * n, &sn, &cs);
  const float e = expf(z.x * n);
  return make_float2(e * cs, e * sn);
}

__global__ void __launch_bounds__(128) gate_kernel(SsmArgs args) {
  const int warp = threadIdx.x >> 5, lane = threadIdx.x & 31;
  const int t0 = blockIdx.x * 32 + warp * 8;
  float acc[8];
#pragma unroll
  for (int tt = 0; tt < 8; tt++) acc[tt] = 0.f;
#pragma unroll
  for (int d = 2 * lane; d < DM; d += 64) {
    const __nv_bfloat162 wv = *reinterpret_cast<const __nv_bfloat162*>(args.gate_w + d);
#pragma unroll
    for (int tt = 0; tt < 8; tt++) {
      const __nv_bfloat162 xv = *reinterpret_cast<const __nv_bfloat162*>(args.x + (size_t)(t0 + tt) * DM + d);
      acc[tt] += rbf(bf2f(xv.x) * bf2f(wv.x)) + rbf(bf2f(xv.y) * bf2f(wv.y));
    }
  }
#pragma unroll
  for (int tt = 0; tt < 8; tt++) {
#pragma unroll
    for (int o = 16; o; o >>= 1) acc[tt] += __shfl_xor_sync(~0u, acc[tt], o);
    if (lane == 0) {
      const float gv = rbf(1.f / (1.f + expf(-rbf(acc[tt]))));
      args.gate[t0 + tt] = gv;
      args.omg[t0 + tt] = rbf(1.f - gv);
    }
  }
}

constexpr int S1_STAGE = 32768, S1_NST = 3, S1_SMEM = S1_NST * S1_STAGE + 256;
__global__ void __launch_bounds__(160, 2)
ssm1_kernel(const __grid_constant__ CUtensorMap tm_bre, const __grid_constant__ CUtensorMap tm_bim, const __grid_constant__ CUtensorMap tm_xp, SsmArgs args) {
  extern __shared__ __align__(1024) uint8_t smem[];
  const uint32_t sb = smem_u32(smem), bar = sb + S1_NST * S1_STAGE;
  const int tid = threadIdx.x, warp = tid >> 5, lane = tid & 31;
  const int cg = blockIdx.x, tc = blockIdx.y;
  KT_START(1);
  if (tid == 0) {
    for (int i = 0; i < 7; i++) mbar_init(bar + i * 8, 1);
    for (int i = 0; i < 3; i++) mbar_init(bar + (8 + i) * 8, 4);
    asm volatile("fence.mbarrier_init.release.cluster;" ::: "memory");
  }
  __syncthreads();
  if (warp == 4) {
    if (lane == 0) {
      for (int kc = 0; kc < 7; kc++) {
        const int st = kc % 3;
        if (kc >= 3) mbar_wait(bar + (8 + st) * 8, ((kc / 3) - 1) & 1);
        mbar_expect_tx(bar + kc * 8, S1_STAGE);
        tma_load_2d(sb + st * S1_STAGE, &tm_bre, kc * 64, cg * 64, bar + kc * 8);
        tma_load_2d(sb + st * S1_STAGE + 8192, &tm_bim, kc * 64, cg * 64, bar + kc * 8);
        tma_load_4d(sb + st * S1_STAGE + 16384, &tm_xp, kc * 64, 0, tc * 4, 0, bar + kc * 8);
      }
    }
    return;
  }
  const int g = lane >> 2, q = lane & 3;
  float2 zz[2]; float lre[2], lim[2];
#pragma unroll
  for (int r = 0; r < 2; r++) { const int ch = cg * 64 + warp * 16 + g + r * 8; zz[r] = ssm_z(args, ch); lre[r] = bf2f(args.lam_re[ch]); lim[r] = bf2f(args.lam_im[ch]); }
  float ur[64], ui[64];
#pragma unroll 1
  for (int kc = 0; kc < 7; kc++) {
    const int st = kc % 3;
    mbar_wait(bar + kc * 8, 0);
    const uint32_t b0 = sb + st * S1_STAGE;
    wg_fence();
#pragma unroll
    for (int kk = 0; kk < 4; kk++) {
      wgmma_ss_n128(ur, desc_sw128(b0 + kk * 32), desc_sw128(b0 + 16384 + kk * 32), (kc | kk) != 0);
      wgmma_ss_n128(ui, desc_sw128(b0 + 8192 + kk * 32), desc_sw128(b0 + 16384 + kk * 32), (kc | kk) != 0);
    }
    wg_commit();
    wg_wait<0>();
    if (lane == 0) mbar_arrive(bar + (8 + st) * 8);
  }
#pragma unroll
  for (int r = 0; r < 2; r++) {
    const int ch = cg * 64 + warp * 16 + g + r * 8;
    const float2 z = zz[r];
    const float2 lam = cexp_n(z, 1.f);
    const float lr = lre[r], li = lim[r];
    const float den = lr * lr + li * li;
    const float2 num = make_float2(lam.x - 1.f, lam.y);
    const float2 coef = make_float2((num.x * lr + num.y * li) / den, (num.y * lr - num.x * li) / den);
    float2 hs = make_float2(0.f, 0.f);
#pragma unroll
    for (int i = 0; i < 32; i++) {
      const int idx = (i >> 1) * 4 + r * 2 + (i & 1);
      const float2 bu = cmul(coef, make_float2(ur[idx], ui[idx]));
      hs = make_float2(fmaf(lam.x, hs.x, fmaf(-lam.y, hs.y, bu.x)), fmaf(lam.x, hs.y, fmaf(lam.y, hs.x, bu.y)));
      ur[idx] = hs.x; ui[idx] = hs.y;
    }
    const float2 l32 = cexp_n(z, 32.f);
    if (tc == 0 && q == 0) {
      const float2 l128 = cexp_n(z, 128.f);
      args.tab[ch * 2] = make_float4(lam.x, lam.y, l32.x, l32.y);
      args.tab[ch * 2 + 1] = make_float4(l128.x, l128.y, 0.f, 0.f);
    }
    float2 carry = make_float2(0.f, 0.f);
#pragma unroll
    for (int qq = 0; qq < 3; qq++) {
      const float ex = __shfl_sync(~0u, hs.x, (lane & ~3) + qq), ey = __shfl_sync(~0u, hs.y, (lane & ~3) + qq);
      if (qq < q) { const float2 t = cmul(l32, carry); carry = make_float2(t.x + ex, t.y + ey); }
    }
    float2 p = lam;
    float4* dre = reinterpret_cast<float4*>(args.hloc) + ((((size_t)tc * 7 + cg) * 4 + warp) * 2 + r) * 256 + lane;
    float4* dim = dre + (size_t)DM * SEQ / 4;
#pragma unroll
    for (int i4 = 0; i4 < 8; i4++) {
      float vr[4], vi[4];
#pragma unroll
      for (int e = 0; e < 4; e++) {
        const int i = i4 * 4 + e, idx = (i >> 1) * 4 + r * 2 + (i & 1);
        const float2 t = cmul(p, carry);
        vr[e] = ur[idx] + t.x; vi[e] = ui[idx] + t.y;
        p = cmul(p, lam);
      }
      dre[i4 * 32] = make_float4(vr[0], vr[1], vr[2], vr[3]);
      dim[i4 * 32] = make_float4(vi[0], vi[1], vi[2], vi[3]);
      if (i4 == 7 && q == 3) args.hend[tc * DM + ch] = make_float2(vr[3], vi[3]);
    }
  }
  KT_END(1);
}

constexpr int S2_A = 896 * 128, S2_NST = 3, S2_SMEM = S2_A + S2_NST * XT_BYTES + 1024;
__global__ void __launch_bounds__(288, 1)
ssm2_kernel(const __grid_constant__ CUtensorMap tm_cre, const __grid_constant__ CUtensorMap tm_cim, SsmArgs args) {
  extern __shared__ __align__(1024) uint8_t smem[];
  const uint32_t sb = smem_u32(smem), bar = sb + S2_A + S2_NST * XT_BYTES;
  float* sg = reinterpret_cast<float*>(smem + S2_A + S2_NST * XT_BYTES + 512);
  const int tid = threadIdx.x, warp = tid >> 5, lane = tid & 31;
  const int t0 = blockIdx.x * 64, chunk = t0 >> 7, tau0 = t0 & 127;
  KT_START(2);
  if (tid == 0) {
    for (int i = 0; i < 28; i++) mbar_init(bar + i * 8, 1);
    for (int i = 0; i < 3; i++) mbar_init(bar + (28 + i) * 8, 4);
    asm volatile("fence.mbarrier_init.release.cluster;" ::: "memory");
  }
  __syncthreads();
  if (warp == 8) {
    if (lane == 0) {
      for (int i = 0; i < 28; i++) {
        const int st = i % 3, kc = i >> 1;
        if (i >= 3) mbar_wait(bar + (28 + st) * 8, ((i / 3) - 1) & 1);
        mbar_expect_tx(bar + i * 8, XT_BYTES);
        tma_load_2d(sb + S2_A + st * XT_BYTES, kc < 7 ? &tm_cre : &tm_cim, (kc % 7) * 64, (i & 1) * 224, bar + i * 8);
      }
    }
    return;
  }
  if (tid < 64) sg[tid] = args.gate[t0 + tid];
  for (int it = tid; it < DM * 2; it += 256) {
    const int qi = it & 1, gg = (it >> 1) & 7, r = (it >> 4) & 1, cw = it >> 5;
    const int ch = cw * 16 + r * 8 + gg;
    const float4 tb0 = args.tab[ch * 2], tb1 = args.tab[ch * 2 + 1];
    float2 e[15];
#pragma unroll
    for (int c = 0; c < 15; c++) e[c] = c < chunk ? args.hend[c * DM + ch] : make_float2(0.f, 0.f);
    const int qq = (tau0 >> 5) + qi;
    const float4* sre = reinterpret_cast<const float4*>(args.hloc) + (((size_t)chunk * 28 + cw) * 2 + r) * 256 + gg * 4 + qq;
    const float4* sim = sre + (size_t)DM * SEQ / 4;
    float4 vr4[8], vi4[8];
#pragma unroll
    for (int i4 = 0; i4 < 8; i4++) { vr4[i4] = sre[i4 * 32]; vi4[i4] = sim[i4 * 32]; }
    const float2 l128 = make_float2(tb1.x, tb1.y), lam = make_float2(tb0.x, tb0.y), l32 = make_float2(tb0.z, tb0.w);
    float2 hin = make_float2(0.f, 0.f);
#pragma unroll
    for (int c = 0; c < 15; c++) if (c < chunk) { const float2 t = cmul(l128, hin); hin = make_float2(t.x + e[c].x, t.y + e[c].y); }
    float2 p = cmul(lam, hin);
    for (int k = 0; k < qq; k++) p = cmul(p, l32);
#pragma unroll
    for (int m = 0; m < 4; m++) {
      float vr[8] = {vr4[2 * m].x, vr4[2 * m].y, vr4[2 * m].z, vr4[2 * m].w, vr4[2 * m + 1].x, vr4[2 * m + 1].y, vr4[2 * m + 1].z, vr4[2 * m + 1].w};
      float vi[8] = {vi4[2 * m].x, vi4[2 * m].y, vi4[2 * m].z, vi4[2 * m].w, vi4[2 * m + 1].x, vi4[2 * m + 1].y, vi4[2 * m + 1].z, vi4[2 * m + 1].w};
#pragma unroll
      for (int k = 0; k < 8; k++) { vr[k] = 2.f * (vr[k] + p.x); vi[k] = -2.f * (vi[k] + p.y); p = cmul(p, lam); }
      const uint4 pr = make_uint4(pack_bf16(vr[0], vr[1]), pack_bf16(vr[2], vr[3]), pack_bf16(vr[4], vr[5]), pack_bf16(vr[6], vr[7]));
      const uint4 pi = make_uint4(pack_bf16(vi[0], vi[1]), pack_bf16(vi[2], vi[3]), pack_bf16(vi[4], vi[5]), pack_bf16(vi[6], vi[7]));
      const int m8 = qi * 4 + m;
      *reinterpret_cast<uint4*>(smem + ch * 128 + ((m8 ^ (ch & 7)) << 4)) = pr;
      *reinterpret_cast<uint4*>(smem + (DM + ch) * 128 + ((m8 ^ (ch & 7)) << 4)) = pi;
    }
  }
  fence_async_smem();
  named_bar(1, 256);
  const int wg = warp >> 2, w = warp & 3;
  float acc[112];
#pragma unroll 1
  for (int kc = 0; kc < 14; kc++) {
    const int i = kc * 2 + wg, st = i % 3;
    mbar_wait(bar + i * 8, 0);
    const uint32_t bb = sb + S2_A + st * XT_BYTES;
    wg_fence();
#pragma unroll
    for (int kk = 0; kk < 4; kk++) {
      const uint64_t da = desc_sw128(sb + (kc * 64 + kk * 16) * 128);
      wgmma_ss_n112_ta(acc, da, desc_sw128(bb + kk * 32), (kc | kk) != 0);
      wgmma_ss_n112_ta(acc + 56, da, desc_sw128(bb + 14336 + kk * 32), (kc | kk) != 0);
    }
    wg_commit();
    wg_wait<0>();
    if (lane == 0) mbar_arrive(bar + (28 + st) * 8);
  }
  const int g = lane >> 2, q = lane & 3;
  named_bar(1, 256);
  float* stg = reinterpret_cast<float*>(smem);
#pragma unroll
  for (int r = 0; r < 2; r++)
#pragma unroll
    for (int nt = 0; nt < 28; nt++)
      *reinterpret_cast<float2*>(stg + (w * 16 + g + r * 8) * 456 + wg * 224 + nt * 8 + 2 * q) = make_float2(acc[nt * 4 + r * 2], acc[nt * 4 + r * 2 + 1]);
  named_bar(1, 256);
  for (int it = tid; it < 64 * 112; it += 256) {
    const int tl = it / 112, d = (it % 112) * 4;
    const float4 y = *reinterpret_cast<const float4*>(stg + tl * 456 + d);
    const uint2 xu = *reinterpret_cast<const uint2*>(args.x + (size_t)(t0 + tl) * DM + d), du = *reinterpret_cast<const uint2*>(args.dskip + d);
    const float gv = sg[tl];
    float4 o;
    o.x = gv * (y.x + rbf(__uint_as_float(xu.x << 16) * __uint_as_float(du.x << 16)));
    o.y = gv * (y.y + rbf(__uint_as_float(xu.x & 0xFFFF0000u) * __uint_as_float(du.x & 0xFFFF0000u)));
    o.z = gv * (y.z + rbf(__uint_as_float(xu.y << 16) * __uint_as_float(du.y << 16)));
    o.w = gv * (y.w + rbf(__uint_as_float(xu.y & 0xFFFF0000u) * __uint_as_float(du.y & 0xFFFF0000u)));
    red_v4(args.out + (size_t)(t0 + tl) * DM + d, o.x, o.y, o.z, o.w);
  }
  KT_END(2);
}
struct AttnArgs {
  uint32_t* flag;
  uint32_t* ticket;
  const float* omg;
  float* out;
  uint32_t total_ctas;
};
#define AT_SPLIT_V 56
constexpr int AT_SPLIT = AT_SPLIT_V;
constexpr int AT_ITEMS = AT_SPLIT * 2 + (NSEG - AT_SPLIT) * 8;
constexpr int AT_X = 2 * 7 * 4096;
constexpr int AT_T = 7 * 5120;
constexpr int AT_OFF_K = AT_X, AT_OFF_Y = AT_X + 2 * AT_T;
constexpr int AT_OFF_P = AT_X + 4 * AT_T;
constexpr int AT_OFF_BAR = AT_OFF_P + 2 * 2 * 3072;
constexpr int AT_STG = 32 * 68 * 4;
constexpr int AT_OFF_STG = AT_OFF_BAR + 256;
constexpr int AT_SMEM = AT_OFF_STG + 2 * AT_STG;
constexpr uint32_t FLAG_TARGET = 112;

__device__ __forceinline__ void attn_decode(int item, int& s, int& p0, int& np) {
  if (item < AT_SPLIT * 2) { s = item >> 1; p0 = (item & 1) * 4; np = 4; }
  else { const int i = item - AT_SPLIT * 2; s = AT_SPLIT + (i >> 3); p0 = i & 7; np = 1; }
}

#define ATS(i) do {} while (0)
__device__ __forceinline__ void attn_consumer(uint8_t* smem, uint32_t sb, const AttnArgs& args, int wg, int w, int lane) {
  const uint32_t bar = sb + AT_OFF_BAR;
  volatile int* s_item = reinterpret_cast<volatile int*>(smem + AT_OFF_BAR + 128);
  float* stg = reinterpret_cast<float*>(smem + AT_OFF_STG + wg * AT_STG);
  const int g = lane >> 2, q = lane & 3;
  const int C0 = wg * 4;
  int m = 0;
  long long tprev = clock64(); (void)tprev;
  for (int n = 0;; n++) {
    mbar_wait(bar + (0 + (n & 1)) * 8, (n >> 1) & 1);
    ATS(0);
    const int item = s_item[n & 1];
    if (item >= AT_ITEMS) break;
    int s, p0, np;
    attn_decode(item, s, p0, np);
    const uint64_t dx = desc_sw128(sb + (n & 1) * (7 * 4096));
    float acc[4][16];
    float om4[4];
#pragma unroll
    for (int i = 0; i < 4; i++) om4[i] = args.omg[s * SEG + i * 8 + ((w * 32 + lane) >> 4)];
#pragma unroll 1
    for (int pp = 0; pp < np; pp++, m++) {
      const uint64_t dk = desc_sw128(sb + AT_OFF_K + wg * AT_T);
      mbar_wait(bar + 4 * 8, m & 1);
      ATS(1);
      float sc[20];
      wg_fence();
#pragma unroll
      for (int kc = 0; kc < 7; kc++)
#pragma unroll
        for (int kk = 0; kk < 4; kk++) wgmma_ss_n40(sc, dx + (uint64_t)(kc * 256 + kk * 2), dk + (uint64_t)(kc * 320 + kk * 2), (kc | kk) != 0);
      wg_commit();
      wg_wait<0>();
      __syncwarp();
      if (lane == 0) { mbar_arrive(bar + 5 * 8); if (pp == np - 1) mbar_arrive(bar + (2 + (n & 1)) * 8); }
      ATS(2);
      const uint32_t pbuf = sb + AT_OFF_P + (m & 1) * (2 * 3072);
      if (w < 2) {
#pragma unroll
        for (int r = 0; r < 2; r++) {
          const int t = w * 16 + g + r * 8;
          float v[10];
          float mx = -3.0e38f;
#pragma unroll
          for (int nt = 0; nt < 5; nt++)
#pragma unroll
            for (int e = 0; e < 2; e++) {
              const int key = nt * 8 + 2 * q + e;
              const float x = (key - NMEM <= t) ? sc[nt * 4 + r * 2 + e] : -1.0e9f;
              v[nt * 2 + e] = x; mx = fmaxf(mx, x);
            }
          mx = fmaxf(mx, __shfl_xor_sync(~0u, mx, 1));
          mx = fmaxf(mx, __shfl_xor_sync(~0u, mx, 2));
          float l = 0.f;
#pragma unroll
          for (int k = 0; k < 10; k++) { v[k] = ex2((v[k] - mx) * L2E); l += v[k]; }
          l += __shfl_xor_sync(~0u, l, 1);
          l += __shfl_xor_sync(~0u, l, 2);
          const float rl = __fdividef(1.f, l);
          const uint32_t dst = pbuf + wg * 3072 + (2 * w + r) * 768 + g * 16 + q * 4;
#pragma unroll
          for (int nt = 0; nt < 5; nt++) asm volatile("st.shared.u32 [%0], %1;" ::"r"(dst + nt * 128), "r"(pack_bf16(v[2 * nt] * rl, v[2 * nt + 1] * rl)) : "memory");
        }
        fence_async_smem();
      }
      ATS(3);
      named_bar(1, 256);
      ATS(4);
      const uint64_t dp = ((uint64_t)((pbuf & 0x3FFFF) >> 4)) | ((uint64_t)(128 >> 4) << 16) | ((uint64_t)(768 >> 4) << 32);
      const uint64_t dy = desc_sw128(sb + AT_OFF_Y);
      mbar_wait(bar + 6 * 8, m & 1);
      ATS(5);
      wg_fence();
#pragma unroll
      for (int c = 0; c < 4; c++) {
        const int cc = min(C0 + c, 6);
#pragma unroll
        for (int hk = 0; hk < 6; hk++) {
          const int hd = hk / 3, kk = hk % 3;
          wgmma_ss_n32_ta(acc[c], dy + (uint64_t)(hd * (AT_T >> 4) + cc * 320 + kk * 128), dp + (uint64_t)(hd * 192 + kk * 16), (pp | hk) != 0);
        }
      }
      wg_commit();
      wg_wait<0>();
      __syncwarp();
      if (lane == 0) mbar_arrive(bar + 7 * 8);
      ATS(6);
    }
    {
      const int tid7 = w * 32 + lane;
#pragma unroll
      for (int c = 0; c < 4; c++) {
        if (C0 + c < 7) {
#pragma unroll
          for (int nt = 0; nt < 4; nt++) {
            stg[(8 * nt + 2 * q) * 68 + 16 * w + g] = acc[c][4 * nt];
            stg[(8 * nt + 2 * q + 1) * 68 + 16 * w + g] = acc[c][4 * nt + 1];
            stg[(8 * nt + 2 * q) * 68 + 16 * w + g + 8] = acc[c][4 * nt + 2];
            stg[(8 * nt + 2 * q + 1) * 68 + 16 * w + g + 8] = acc[c][4 * nt + 3];
          }
          named_bar(2 + wg, 128);
#pragma unroll
          for (int i = 0; i < 4; i++) {
            const int row = i * 8 + (tid7 >> 4), col = (tid7 & 15) * 4;
            const float4 v = *reinterpret_cast<const float4*>(stg + row * 68 + col);
            const float om = om4[i];
            red_v4(args.out + (size_t)(s * SEG + row) * DM + (C0 + c) * 64 + col, om * v.x, om * v.y, om * v.z, om * v.w);
          }
          named_bar(2 + wg, 128);
        }
      }
    }
    ATS(7);
  }
}

__global__ void __launch_bounds__(384, 1)
attn_kernel(const __grid_constant__ CUtensorMap tm_x, const __grid_constant__ CUtensorMap tm_k, const __grid_constant__ CUtensorMap tm_y, AttnArgs args) {
  extern __shared__ __align__(1024) uint8_t smem[];
  const uint32_t sb = smem_u32(smem), bar = sb + AT_OFF_BAR;
  volatile int* s_item = reinterpret_cast<volatile int*>(smem + AT_OFF_BAR + 128);
  const int tid = threadIdx.x, warp = tid >> 5, lane = tid & 31;
  KT_START(3);
  if (tid == 0) {
    mbar_init(bar + 0 * 8, 1); mbar_init(bar + 1 * 8, 1); mbar_init(bar + 2 * 8, 8); mbar_init(bar + 3 * 8, 8);
    mbar_init(bar + 4 * 8, 1); mbar_init(bar + 5 * 8, 8); mbar_init(bar + 6 * 8, 1); mbar_init(bar + 7 * 8, 8);
    asm volatile("fence.mbarrier_init.release.cluster;" ::: "memory");
  }
  for (int i = tid; i < AT_OFF_BAR / 16; i += 384) *reinterpret_cast<uint4*>(smem + i * 16) = make_uint4(0, 0, 0, 0);
  fence_async_smem();
  __syncthreads();
  const int wg = __shfl_sync(0xffffffffu, warp >> 2, 0);
  if (wg == 2) {
    asm volatile("setmaxnreg.dec.sync.aligned.u32 40;");
    if (tid == 256) {
      int m = 0;
      for (int n = 0;; n++) {
        const int sl = n & 1;
        if (n >= 2) mbar_wait(bar + (2 + sl) * 8, ((n >> 1) - 1) & 1);
        const int item = (int)atomicAdd(args.ticket, 1u);
        s_item[sl] = item;
        if (item >= AT_ITEMS) {
          mbar_arrive(bar + sl * 8);
          if (atomicAdd(args.ticket + 1, 1u) == args.total_ctas - 1) {
            for (int i = 0; i < NSEG; i++) args.flag[i] = 0u;
            args.ticket[0] = 0u; args.ticket[1] = 0u;
          }
          break;
        }
        int s, p0, np;
        attn_decode(item, s, p0, np);
        mbar_expect_tx(bar + sl * 8, 7 * 4096);
        tma_load_3d(sb + sl * (7 * 4096), &tm_x, 0, s * SEG, 0, bar + sl * 8);
        { int it = 0; while (ld_acquire(args.flag + s) < FLAG_TARGET && ++it < SPIN_LIMIT) __nanosleep(100); }
        fence_async_all();
        for (int pp = 0; pp < np; pp++, m++) {
          const int row = (((p0 + pp) * 2) * NSEG + s) * LKEY;
          if (m >= 1) mbar_wait(bar + 5 * 8, (m - 1) & 1);
          mbar_expect_tx(bar + 4 * 8, 2 * AT_T);
          tma_load_3d(sb + AT_OFF_K, &tm_k, 0, row, 0, bar + 4 * 8);
          tma_load_3d(sb + AT_OFF_K + AT_T, &tm_k, 0, row + NSEG * LKEY, 0, bar + 4 * 8);
          if (m >= 1) mbar_wait(bar + 7 * 8, (m - 1) & 1);
          mbar_expect_tx(bar + 6 * 8, 2 * AT_T);
          tma_load_3d(sb + AT_OFF_Y, &tm_y, 0, row, 0, bar + 6 * 8);
          tma_load_3d(sb + AT_OFF_Y + AT_T, &tm_y, 0, row + NSEG * LKEY, 0, bar + 6 * 8);
        }
      }
    }
  } else {
    asm volatile("setmaxnreg.inc.sync.aligned.u32 232;");
    attn_consumer(smem, sb, args, wg, warp & 3, lane);
    KT_END(3);
  }
}
__device__ bf16 g_Kall[(size_t)NH * NSEG * LKEY * DM];
__device__ bf16 g_Yall[(size_t)NH * NSEG * LKEY * DM];
__device__ uint32_t g_M[65 * 1792];
__device__ float4 g_S[(size_t)NSEG * NH * 5 * 32 + (size_t)NSEG * NJ * 16 * 16 * 8];
__device__ uint32_t g_flag[NSEG + 64];
__device__ float g_hloc[2 * DM * SEQ];
__device__ float2 g_hend[16 * DM];
__device__ float g_omg[2 * SEQ];
__device__ float4 g_tab[2 * DM];
__device__ uint32_t g_dbg[112 * 1024 + 112 * 4 + 112 * 8];

typedef CUresult (*EncodeFn)(CUtensorMap*, CUtensorMapDataType, cuuint32_t, void*, const cuuint64_t*, const cuuint64_t*, const cuuint32_t*,
                             const cuuint32_t*, CUtensorMapInterleave, CUtensorMapSwizzle, CUtensorMapL2promotion, CUtensorMapFloatOOBfill);

static bool make_map_2d(EncodeFn enc, CUtensorMap* m, const void* ptr, uint64_t cols, uint64_t rows, uint32_t box_cols, uint32_t box_rows) {
  cuuint64_t dims[2] = {cols, rows};
  cuuint64_t strides[1] = {cols * 2};
  cuuint32_t box[2] = {box_cols, box_rows};
  cuuint32_t es[2] = {1, 1};
  return enc(m, CU_TENSOR_MAP_DATA_TYPE_BFLOAT16, 2, const_cast<void*>(ptr), dims, strides, box, es, CU_TENSOR_MAP_INTERLEAVE_NONE,
             CU_TENSOR_MAP_SWIZZLE_128B, CU_TENSOR_MAP_L2_PROMOTION_L2_256B, CU_TENSOR_MAP_FLOAT_OOB_FILL_NONE) == CUDA_SUCCESS;
}
static bool make_map_rows(EncodeFn enc, CUtensorMap* m, const void* ptr, uint64_t rows, uint32_t box_rows) {
  cuuint64_t dims[3] = {64, rows, 7};
  cuuint64_t strides[2] = {(cuuint64_t)DM * 2, 128};
  cuuint32_t box[3] = {64, box_rows, 7};
  cuuint32_t es[3] = {1, 1, 1};
  return enc(m, CU_TENSOR_MAP_DATA_TYPE_BFLOAT16, 3, const_cast<void*>(ptr), dims, strides, box, es, CU_TENSOR_MAP_INTERLEAVE_NONE,
             CU_TENSOR_MAP_SWIZZLE_128B, CU_TENSOR_MAP_L2_PROMOTION_L2_256B, CU_TENSOR_MAP_FLOAT_OOB_FILL_NONE) == CUDA_SUCCESS;
}
static bool make_map_xperm(EncodeFn enc, CUtensorMap* m, const void* ptr) {
  cuuint64_t dims[4] = {(cuuint64_t)DM, 2, 64, 16};
  cuuint64_t strides[3] = {(cuuint64_t)DM * 2, (cuuint64_t)DM * 2 * 32, (cuuint64_t)DM * 2 * 2};
  cuuint32_t box[4] = {64, 2, 4, 16};
  cuuint32_t es[4] = {1, 1, 1, 1};
  return enc(m, CU_TENSOR_MAP_DATA_TYPE_BFLOAT16, 4, const_cast<void*>(ptr), dims, strides, box, es, CU_TENSOR_MAP_INTERLEAVE_NONE,
             CU_TENSOR_MAP_SWIZZLE_128B, CU_TENSOR_MAP_L2_PROMOTION_L2_256B, CU_TENSOR_MAP_FLOAT_OOB_FILL_NONE) == CUDA_SUCCESS;
}

#define N_ATTN 7
struct HostState {
  bool init, ok, use_cluster;
  CUtensorMap tx, tq, tk, tv, to, tka, tya, tbre, tbim, txp, tcre, tcim, tx3, tk3, ty3;
  void *pK, *pY, *pM, *pS, *pF, *pD, *pH, *pE, *pO, *pT;
  cudaStream_t side, side2;
  cudaEvent_t ev_start, ev_join, ev_gate, ev_join2;
  int n_free, n_attn;
  const void* key[17];
  void* key_out;
};
static HostState g_hs;

}

extern "C" void kernel_launch(void* const* d_in, const int* in_sizes, int n_in, void* d_out, int out_size) {
  HostState& S = g_hs;
  (void)in_sizes; (void)n_in; (void)out_size;
  cudaStream_t st = cudaStreamPerThread;
  bool same = S.init;
  for (int i = 0; i < 17 && same; i++) same = S.key[i] == d_in[i];
  if (!same) {
    EncodeFn enc = nullptr;
    cudaDriverEntryPointQueryResult qr;
    cudaGetDriverEntryPoint("cuTensorMapEncodeTiled", (void**)&enc, cudaEnableDefault, &qr);
    cudaGetSymbolAddress(&S.pK, g_Kall); cudaGetSymbolAddress(&S.pY, g_Yall); cudaGetSymbolAddress(&S.pM, g_M); cudaGetSymbolAddress(&S.pS, g_S);
    cudaGetSymbolAddress(&S.pF, g_flag); cudaGetSymbolAddress(&S.pD, g_dbg); cudaGetSymbolAddress(&S.pH, g_hloc); cudaGetSymbolAddress(&S.pE, g_hend);
    cudaGetSymbolAddress(&S.pO, g_omg); cudaGetSymbolAddress(&S.pT, g_tab);
    S.ok = enc && make_map_2d(enc, &S.tx, d_in[0], DM, SEQ, 64, 32) && make_map_2d(enc, &S.tq, d_in[11], 4096, DM, 64, 64) &&
           make_map_2d(enc, &S.tk, d_in[12], 4096, DM, 64, 224) && make_map_2d(enc, &S.tv, d_in[13], 4096, DM, 64, 224) &&
           make_map_2d(enc, &S.to, d_in[14], DM, 4096, 64, 256) && make_map_2d(enc, &S.tka, S.pK, DM, NH * NSEG * LKEY, 64, LKEY) &&
           make_map_2d(enc, &S.tya, S.pY, DM, NH * NSEG * LKEY, 64, LKEY) && make_map_2d(enc, &S.tbre, d_in[3], DM, DM, 64, 64) &&
           make_map_2d(enc, &S.tbim, d_in[4], DM, DM, 64, 64) && make_map_xperm(enc, &S.txp, d_in[0]) &&
           make_map_2d(enc, &S.tcre, d_in[5], DM, DM, 64, 224) && make_map_2d(enc, &S.tcim, d_in[6], DM, DM, 64, 224) &&
           make_map_rows(enc, &S.tx3, d_in[0], SEQ, SEG) && make_map_rows(enc, &S.tk3, S.pK, NH * NSEG * LKEY, LKEY) && make_map_rows(enc, &S.ty3, S.pY, NH * NSEG * LKEY, LKEY);
    if (!S.init) {
      cudaFuncSetAttribute(chain_kernel<true>, cudaFuncAttributeMaxDynamicSharedMemorySize, SMEM_CHAIN);
      cudaFuncSetAttribute(chain_kernel<true>, cudaFuncAttributeNonPortableClusterSizeAllowed, 1);
      cudaFuncSetAttribute(chain_kernel<false>, cudaFuncAttributeMaxDynamicSharedMemorySize, SMEM_CHAIN);
      cudaFuncSetAttribute(ssm1_kernel, cudaFuncAttributeMaxDynamicSharedMemorySize, S1_SMEM);
      cudaFuncSetAttribute(ssm2_kernel, cudaFuncAttributeMaxDynamicSharedMemorySize, S2_SMEM);
      cudaFuncSetAttribute(attn_kernel, cudaFuncAttributeMaxDynamicSharedMemorySize, AT_SMEM);
      cudaLaunchConfig_t cfg = {};
      cfg.gridDim = dim3(112); cfg.blockDim = dim3(CHAIN_THREADS); cfg.dynamicSmemBytes = SMEM_CHAIN;
      cudaLaunchAttribute at[1];
      at[0].id = cudaLaunchAttributeClusterDimension; at[0].val.clusterDim.x = 16; at[0].val.clusterDim.y = 1; at[0].val.clusterDim.z = 1;
      cfg.attrs = at; cfg.numAttrs = 1;
      int nc = 0;
      if (cudaOccupancyMaxActiveClusters(&nc, chain_kernel<true>, &cfg) != cudaSuccess) { nc = 0; (void)cudaGetLastError(); }
      S.use_cluster = nc >= 7;
      int sms = 132;
      cudaDeviceGetAttribute(&sms, cudaDevAttrMultiProcessorCount, 0);
      S.n_free = sms - 112 > 1 ? sms - 112 : 1;
      S.n_attn = S.n_free >= 16 ? N_ATTN : (S.n_free + 1) / 2;
      cudaStreamCreateWithFlags(&S.side, cudaStreamNonBlocking);
      cudaEventCreateWithFlags(&S.ev_start, cudaEventDisableTiming);
      cudaEventCreateWithFlags(&S.ev_join, cudaEventDisableTiming);
      cudaStreamCreateWithFlags(&S.side2, cudaStreamNonBlocking);
      cudaEventCreateWithFlags(&S.ev_gate, cudaEventDisableTiming);
      cudaEventCreateWithFlags(&S.ev_join2, cudaEventDisableTiming);
    }
    for (int i = 0; i < 17; i++) S.key[i] = d_in[i];
    S.init = true;
  }
  if (!S.ok) return;

  ChainArgs ca;
  ca.mem0 = (const bf16*)d_in[10]; ca.Mg = (uint32_t*)S.pM; ca.Sg = (float4*)S.pS; ca.flag = (uint32_t*)S.pF; ca.dbg = (uint32_t*)S.pD;
  {
    cudaLaunchConfig_t cfg = {};
    cfg.gridDim = dim3(112); cfg.blockDim = dim3(CHAIN_THREADS); cfg.dynamicSmemBytes = SMEM_CHAIN; cfg.stream = st;
    cudaLaunchAttribute at[2];
    at[0].id = cudaLaunchAttributeLaunchCompletionEvent; at[0].val.launchCompletionEvent.event = S.ev_start; at[0].val.launchCompletionEvent.flags = 0;
    at[1].id = cudaLaunchAttributeClusterDimension; at[1].val.clusterDim.x = 16; at[1].val.clusterDim.y = 1; at[1].val.clusterDim.z = 1;
    cfg.attrs = at; cfg.numAttrs = S.use_cluster ? 2 : 1;
    if (S.use_cluster) cudaLaunchKernelEx(&cfg, chain_kernel<true>, S.tx, S.tq, S.tk, S.tv, S.to, S.tka, S.tya, S.tx3, ca);
    else cudaLaunchKernelEx(&cfg, chain_kernel<false>, S.tx, S.tq, S.tk, S.tv, S.to, S.tka, S.tya, S.tx3, ca);
  }
  SsmArgs sa;
  sa.lam_re = (const bf16*)d_in[1]; sa.lam_im = (const bf16*)d_in[2]; sa.log_dt = (const bf16*)d_in[7]; sa.dskip = (const bf16*)d_in[8];
  sa.x = (const bf16*)d_in[0]; sa.gate_w = (const bf16*)d_in[16];
  sa.hloc = (float*)S.pH; sa.hend = (float2*)S.pE; sa.omg = (float*)S.pO; sa.gate = (float*)S.pO + SEQ; sa.tab = (float4*)S.pT; sa.out = (float*)d_out;
  AttnArgs aa;
  aa.flag = (uint32_t*)S.pF; aa.ticket = (uint32_t*)S.pF + NSEG; aa.omg = (const float*)S.pO; aa.out = (float*)d_out;
  const int n_attn2 = S.n_free - S.n_attn > 0 ? S.n_free - S.n_attn : 0;
  aa.total_ctas = (uint32_t)(S.n_attn + n_attn2);
  cudaStreamWaitEvent(S.side, S.ev_start, 0);
  cudaMemsetAsync(d_out, 0, sizeof(float) * SEQ * DM, S.side);
  gate_kernel<<<64, 128, 0, S.side>>>(sa);
  cudaEventRecord(S.ev_gate, S.side);
  attn_kernel<<<S.n_attn, 384, AT_SMEM, S.side>>>(S.tx3, S.tk3, S.ty3, aa);
  cudaStreamWaitEvent(S.side2, S.ev_gate, 0);
  ssm1_kernel<<<dim3(7, 16), 160, S1_SMEM, S.side2>>>(S.tbre, S.tbim, S.txp, sa);
  ssm2_kernel<<<32, 288, S2_SMEM, S.side2>>>(S.tcre, S.tcim, sa);
  if (n_attn2 > 0) attn_kernel<<<n_attn2, 384, AT_SMEM, S.side2>>>(S.tx3, S.tk3, S.ty3, aa);
  cudaEventRecord(S.ev_join, S.side);
  cudaEventRecord(S.ev_join2, S.side2);
  cudaStreamWaitEvent(st, S.ev_join, 0);
  cudaStreamWaitEvent(st, S.ev_join2, 0);
}
```

```cpp
#include <cuda_runtime.h>
#include <cuda_bf16.h>
#include <cuda.h>
#include <stdint.h>

typedef __nv_bfloat16 bf16;

namespace {

constexpr int NH = 16, DM = 448, DH = 256, SEQ = 2048, SEG = 32, NSEG = 64, NJ = 7, NMEM = 8, LKEY = 40;
constexpr int SPIN_LIMIT = 1 << 22;

#define KT_START(k) do {} while (0)
#define KT_END(k) do {} while (0)

__device__ __forceinline__ uint32_t smem_u32(const void* p) { return (uint32_t)__cvta_generic_to_shared(p); }
__device__ __forceinline__ void mbar_init(uint32_t a, uint32_t c) { asm volatile("mbarrier.init.shared.b64 [%0], %1;" ::"r"(a), "r"(c)); }
__device__ __forceinline__ void mbar_arrive(uint32_t a) { asm volatile("mbarrier.arrive.shared.b64 _, [%0];" ::"r"(a) : "memory"); }
__device__ __forceinline__ void mbar_expect_tx(uint32_t a, uint32_t b) { asm volatile("mbarrier.arrive.expect_tx.shared.b64 _, [%0], %1;" ::"r"(a), "r"(b) : "memory"); }
__device__ __forceinline__ bool mbar_try(uint32_t a, uint32_t parity) {
  uint32_t r;
  asm volatile("{\n.reg .pred p;\nmbarrier.try_wait.parity.shared.b64 p, [%1], %2;\nselp.u32 %0, 1, 0, p;\n}\n" : "=r"(r) : "r"(a), "r"(parity) : "memory");
  return r;
}
__device__ __forceinline__ bool mbar_try_cluster(uint32_t a, uint32_t parity) {
  uint32_t r;
  asm volatile("{\n.reg .pred p;\nmbarrier.try_wait.parity.acquire.cluster.shared.b64 p, [%1], %2;\nselp.u32 %0, 1, 0, p;\n}\n" : "=r"(r) : "r"(a), "r"(parity) : "memory");
  return r;
}
__device__ __forceinline__ bool mbar_test(uint32_t a, uint32_t parity) {
  uint32_t r;
  asm volatile("{\n.reg .pred p;\nmbarrier.test_wait.parity.shared.b64 p, [%1], %2;\nselp.u32 %0, 1, 0, p;\n}\n" : "=r"(r) : "r"(a), "r"(parity) : "memory");
  return r;
}
__device__ __forceinline__ void mbar_wait(uint32_t a, uint32_t parity) {
  int it = 0;
  while (!mbar_try(a, parity)) { if (++it > SPIN_LIMIT) break; }
}
__device__ __forceinline__ void mbar_wait_cluster(uint32_t a, uint32_t parity) {
  int it = 0;
  while (!mbar_try_cluster(a, parity)) { if (++it > SPIN_LIMIT) break; }
}
__device__ __forceinline__ uint32_t mapa(uint32_t a, uint32_t r) { uint32_t d; asm volatile("mapa.shared::cluster.u32 %0, %1, %2;" : "=r"(d) : "r"(a), "r"(r)); return d; }
__device__ __forceinline__ void cluster_sync_all() { asm volatile("barrier.cluster.arrive.aligned;\nbarrier.cluster.wait.aligned;" ::: "memory"); }
__device__ __forceinline__ void named_bar(int id, int n) { asm volatile("bar.sync %0, %1;" ::"r"(id), "r"(n) : "memory"); }
__device__ __forceinline__ void fence_async_smem() { asm volatile("fence.proxy.async.shared::cta;" ::: "memory"); }
__device__ __forceinline__ void fence_async_all() { asm volatile("fence.proxy.async;" ::: "memory"); }

__device__ __forceinline__ uint4 ld_vol_v4(const void* p) {
  uint4 v;
  asm volatile("ld.volatile.global.v4.u32 {%0,%1,%2,%3}, [%4];" : "=r"(v.x), "=r"(v.y), "=r"(v.z), "=r"(v.w) : "l"(p) : "memory");
  return v;
}
__device__ __forceinline__ uint32_t ld_acquire(const void* p) { uint32_t v; asm volatile("ld.acquire.gpu.global.u32 %0, [%1];" : "=r"(v) : "l"(p) : "memory"); return v; }
__device__ __forceinline__ void st_relaxed(void* p, uint32_t v) { asm volatile("st.relaxed.gpu.global.u32 [%0], %1;" ::"l"(p), "r"(v) : "memory"); }
__device__ __forceinline__ void red_v4(void* p, float a, float b, float c, float d) {
  asm volatile("red.relaxed.gpu.global.add.v4.f32 [%0], {%1,%2,%3,%4};" ::"l"(p), "f"(a), "f"(b), "f"(c), "f"(d) : "memory");
}
__device__ __forceinline__ void red_v2(void* p, float a, float b) {
  asm volatile("red.relaxed.gpu.global.add.v2.f32 [%0], {%1,%2};" ::"l"(p), "f"(a), "f"(b) : "memory");
}
__device__ __forceinline__ void red_u32(void* p, uint32_t v) { asm volatile("red.relaxed.gpu.global.add.u32 [%0], %1;" ::"l"(p), "r"(v) : "memory"); }
__device__ __forceinline__ void st_async_v4(uint32_t addr, float a, float b, float c, float d, uint32_t mbar) {
  asm volatile("st.async.shared::cluster.mbarrier::complete_tx::bytes.v4.f32 [%0], {%1,%2,%3,%4}, [%5];" ::"r"(addr), "f"(a), "f"(b), "f"(c), "f"(d), "r"(mbar) : "memory");
}

__device__ __forceinline__ void tma_load_2d(uint32_t dst, const CUtensorMap* tm, int c0, int c1, uint32_t mbar) {
  asm volatile("cp.async.bulk.tensor.2d.shared::cluster.global.mbarrier::complete_tx::bytes [%0], [%1, {%3, %4}], [%2];" ::"r"(dst), "l"(tm), "r"(mbar), "r"(c0), "r"(c1) : "memory");
}
__device__ __forceinline__ void tma_load_2d_mc(uint32_t dst, const CUtensorMap* tm, int c0, int c1, uint32_t mbar, uint16_t mask) {
  asm volatile("cp.async.bulk.tensor.2d.shared::cluster.global.mbarrier::complete_tx::bytes.multicast::cluster [%0], [%1, {%3, %4}], [%2], %5;" ::"r"(dst), "l"(tm), "r"(mbar), "r"(c0), "r"(c1), "h"(mask) : "memory");
}
__device__ __forceinline__ void tma_load_3d(uint32_t dst, const CUtensorMap* tm, int c0, int c1, int c2, uint32_t mbar) {
  asm volatile("cp.async.bulk.tensor.3d.shared::cluster.global.mbarrier::complete_tx::bytes [%0], [%1, {%3, %4, %5}], [%2];" ::"r"(dst), "l"(tm), "r"(mbar), "r"(c0), "r"(c1), "r"(c2) : "memory");
}
__device__ __forceinline__ void tma_load_4d(uint32_t dst, const CUtensorMap* tm, int c0, int c1, int c2, int c3, uint32_t mbar) {
  asm volatile("cp.async.bulk.tensor.4d.shared::cluster.global.mbarrier::complete_tx::bytes [%0], [%1, {%3, %4, %5, %6}], [%2];" ::"r"(dst), "l"(tm), "r"(mbar), "r"(c0), "r"(c1), "r"(c2), "r"(c3) : "memory");
}
__device__ __forceinline__ void tma_store_2d(const CUtensorMap* tm, int c0, int c1, uint32_t src) {
  asm volatile("cp.async.bulk.tensor.2d.global.shared::cta.bulk_group [%0, {%2, %3}], [%1];" ::"l"(tm), "r"(src), "r"(c0), "r"(c1) : "memory");
}
__device__ __forceinline__ void bulk_load(uint32_t dst, const void* src, uint32_t bytes, uint32_t mbar) {
  asm volatile("cp.async.bulk.shared::cluster.global.mbarrier::complete_tx::bytes [%0], [%1], %2, [%3];" ::"r"(dst), "l"(src), "r"(bytes), "r"(mbar) : "memory");
}
__device__ __forceinline__ void bulk_commit() { asm volatile("cp.async.bulk.commit_group;" ::: "memory"); }
template <int N> __device__ __forceinline__ void bulk_wait_read() { asm volatile("cp.async.bulk.wait_group.read %0;" ::"n"(N) : "memory"); }
template <int N> __device__ __forceinline__ void bulk_wait() { asm volatile("cp.async.bulk.wait_group %0;" ::"n"(N) : "memory"); }

__device__ __forceinline__ void wg_fence() { asm volatile("wgmma.fence.sync.aligned;" ::: "memory"); }
__device__ __forceinline__ void wg_commit() { asm volatile("wgmma.commit_group.sync.aligned;" ::: "memory"); }
template <int N> __device__ __forceinline__ void wg_wait() { asm volatile("wgmma.wait_group.sync.aligned %0;" ::"n"(N) : "memory"); }

__device__ __forceinline__ uint64_t desc_sw128(uint32_t addr) {
  return ((uint64_t)((addr & 0x3FFFF) >> 4)) | ((uint64_t)1 << 16) | ((uint64_t)(1024 >> 4) << 32) | ((uint64_t)1 << 62);
}

__device__ __forceinline__ uint32_t pack_bf16(float lo, float hi) {
  uint32_t r;
  asm("cvt.rn.bf16x2.f32 %0, %1, %2;" : "=r"(r) : "f"(hi), "f"(lo));
  return r;
}
__device__ __forceinline__ void mma16816(float* d, uint32_t a0, uint32_t a1, uint32_t a2, uint32_t a3, uint32_t b0, uint32_t b1) {
  asm volatile("mma.sync.aligned.m16n8k16.row.col.f32.bf16.bf16.f32 {%0,%1,%2,%3}, {%4,%5,%6,%7}, {%8,%9}, {%0,%1,%2,%3};"
               : "+f"(d[0]), "+f"(d[1]), "+f"(d[2]), "+f"(d[3]) : "r"(a0), "r"(a1), "r"(a2), "r"(a3), "r"(b0), "r"(b1));
}
__device__ __forceinline__ void mma1688(float* d, uint32_t a0, uint32_t a1, uint32_t b0) {
  asm volatile("mma.sync.aligned.m16n8k8.row.col.f32.bf16.bf16.f32 {%0,%1,%2,%3}, {%4,%5}, {%6}, {%0,%1,%2,%3};"
               : "+f"(d[0]), "+f"(d[1]), "+f"(d[2]), "+f"(d[3]) : "r"(a0), "r"(a1), "r"(b0));
}
__device__ __forceinline__ void ldsm_x4(uint32_t* r, uint32_t addr) {
  asm volatile("ldmatrix.sync.aligned.m8n8.x4.shared.b16 {%0,%1,%2,%3}, [%4];" : "=r"(r[0]), "=r"(r[1]), "=r"(r[2]), "=r"(r[3]) : "r"(addr) : "memory");
}
__device__ __forceinline__ void ldsm_x4_t(uint32_t* r, uint32_t addr) {
  asm volatile("ldmatrix.sync.aligned.m8n8.x4.trans.shared.b16 {%0,%1,%2,%3}, [%4];" : "=r"(r[0]), "=r"(r[1]), "=r"(r[2]), "=r"(r[3]) : "r"(addr) : "memory");
}
__device__ __forceinline__ void ldsm_x2_t(uint32_t* r, uint32_t addr) {
  asm volatile("ldmatrix.sync.aligned.m8n8.x2.trans.shared.b16 {%0,%1}, [%2];" : "=r"(r[0]), "=r"(r[1]) : "r"(addr) : "memory");
}
__device__ __forceinline__ void stsm_x4_t(uint32_t addr, uint32_t r0, uint32_t r1, uint32_t r2, uint32_t r3) {
  asm volatile("stmatrix.sync.aligned.m8n8.x4.trans.shared.b16 [%0], {%1,%2,%3,%4};" ::"r"(addr), "r"(r0), "r"(r1), "r"(r2), "r"(r3) : "memory");
}
__device__ __forceinline__ uint32_t movm_t(uint32_t a) { uint32_t d; asm volatile("movmatrix.sync.aligned.m8n8.trans.b16 %0, %1;" : "=r"(d) : "r"(a)); return d; }
__device__ __forceinline__ float ex2(float x) { float y; asm("ex2.approx.ftz.f32 %0, %1;" : "=f"(y) : "f"(x)); return y; }

__device__ __forceinline__ void wgmma_ss_n112(float* d, uint64_t descA, uint64_t descB, int scaleD) {
  asm volatile("{\n.reg .pred p;\nsetp.ne.b32 p, %58, 0;\n"
    "wgmma.mma_async.sync.aligned.m64n112k16.f32.bf16.bf16 {%0,%1,%2,%3,%4,%5,%6,%7,%8,%9,%10,%11,%12,%13,%14,%15,%16,%17,%18,%19,%20,%21,%22,%23,%24,%25,%26,%27,%28,%29,%30,%31,%32,%33,%34,%35,%36,%37,%38,%39,%40,%41,%42,%43,%44,%45,%46,%47,%48,%49,%50,%51,%52,%53,%54,%55}, %56, %57, p, 1, 1, 0, 0;\n}\n"
    : "+f"(d[0]),"+f"(d[1]),"+f"(d[2]),"+f"(d[3]),"+f"(d[4]),"+f"(d[5]),"+f"(d[6]),"+f"(d[7]),"+f"(d[8]),"+f"(d[9]),"+f"(d[10]),"+f"(d[11]),"+f"(d[12]),"+f"(d[13]),"+f"(d[14]),"+f"(d[15]),"+f"(d[16]),"+f"(d[17]),"+f"(d[18]),"+f"(d[19]),"+f"(d[20]),"+f"(d[21]),"+f"(d[22]),"+f"(d[23]),"+f"(d[24]),"+f"(d[25]),"+f"(d[26]),"+f"(d[27]),"+f"(d[28]),"+f"(d[29]),"+f"(d[30]),"+f"(d[31]),"+f"(d[32]),"+f"(d[33]),"+f"(d[34]),"+f"(d[35]),"+f"(d[36]),"+f"(d[37]),"+f"(d[38]),"+f"(d[39]),"+f"(d[40]),"+f"(d[41]),"+f"(d[42]),"+f"(d[43]),"+f"(d[44]),"+f"(d[45]),"+f"(d[46]),"+f"(d[47]),"+f"(d[48]),"+f"(d[49]),"+f"(d[50]),"+f"(d[51]),"+f"(d[52]),"+f"(d[53]),"+f"(d[54]),"+f"(d[55])
    : "l"(descA), "l"(descB), "r"(scaleD));
}
__device__ __forceinline__ void wgmma_ss_n112_ta(float* d, uint64_t descA, uint64_t descB, int scaleD) {
  asm volatile("{\n.reg .pred p;\nsetp.ne.b32 p, %58, 0;\n"
    "wgmma.mma_async.sync.aligned.m64n112k16.f32.bf16.bf16 {%0,%1,%2,%3,%4,%5,%6,%7,%8,%9,%10,%11,%12,%13,%14,%15,%16,%17,%18,%19,%20,%21,%22,%23,%24,%25,%26,%27,%28,%29,%30,%31,%32,%33,%34,%35,%36,%37,%38,%39,%40,%41,%42,%43,%44,%45,%46,%47,%48,%49,%50,%51,%52,%53,%54,%55}, %56, %57, p, 1, 1, 1, 0;\n}\n"
    : "+f"(d[0]),"+f"(d[1]),"+f"(d[2]),"+f"(d[3]),"+f"(d[4]),"+f"(d[5]),"+f"(d[6]),"+f"(d[7]),"+f"(d[8]),"+f"(d[9]),"+f"(d[10]),"+f"(d[11]),"+f"(d[12]),"+f"(d[13]),"+f"(d[14]),"+f"(d[15]),"+f"(d[16]),"+f"(d[17]),"+f"(d[18]),"+f"(d[19]),"+f"(d[20]),"+f"(d[21]),"+f"(d[22]),"+f"(d[23]),"+f"(d[24]),"+f"(d[25]),"+f"(d[26]),"+f"(d[27]),"+f"(d[28]),"+f"(d[29]),"+f"(d[30]),"+f"(d[31]),"+f"(d[32]),"+f"(d[33]),"+f"(d[34]),"+f"(d[35]),"+f"(d[36]),"+f"(d[37]),"+f"(d[38]),"+f"(d[39]),"+f"(d[40]),"+f"(d[41]),"+f"(d[42]),"+f"(d[43]),"+f"(d[44]),"+f"(d[45]),"+f"(d[46]),"+f"(d[47]),"+f"(d[48]),"+f"(d[49]),"+f"(d[50]),"+f"(d[51]),"+f"(d[52]),"+f"(d[53]),"+f"(d[54]),"+f"(d[55])
    : "l"(descA), "l"(descB), "r"(scaleD));
}
__device__ __forceinline__ void wgmma_rs_n32(float* d, const uint32_t* a, uint64_t descB, int scaleD) {
  asm volatile("{\n.reg .pred p;\nsetp.ne.b32 p, %21, 0;\n"
    "wgmma.mma_async.sync.aligned.m64n32k16.f32.bf16.bf16 {%0,%1,%2,%3,%4,%5,%6,%7,%8,%9,%10,%11,%12,%13,%14,%15}, {%16,%17,%18,%19}, %20, p, 1, 1, 0;\n}\n"
    : "+f"(d[0]),"+f"(d[1]),"+f"(d[2]),"+f"(d[3]),"+f"(d[4]),"+f"(d[5]),"+f"(d[6]),"+f"(d[7]),"+f"(d[8]),"+f"(d[9]),"+f"(d[10]),"+f"(d[11]),"+f"(d[12]),"+f"(d[13]),"+f"(d[14]),"+f"(d[15])
    : "r"(a[0]), "r"(a[1]), "r"(a[2]), "r"(a[3]), "l"(descB), "r"(scaleD));
}
__device__ __forceinline__ void wgmma_ss_n128(float* d, uint64_t descA, uint64_t descB, int scaleD) {
  asm volatile("{\n.reg .pred p;\nsetp.ne.b32 p, %66, 0;\n"
    "wgmma.mma_async.sync.aligned.m64n128k16.f32.bf16.bf16 {%0,%1,%2,%3,%4,%5,%6,%7,%8,%9,%10,%11,%12,%13,%14,%15,%16,%17,%18,%19,%20,%21,%22,%23,%24,%25,%26,%27,%28,%29,%30,%31,%32,%33,%34,%35,%36,%37,%38,%39,%40,%41,%42,%43,%44,%45,%46,%47,%48,%49,%50,%51,%52,%53,%54,%55,%56,%57,%58,%59,%60,%61,%62,%63}, %64, %65, p, 1, 1, 0, 0;\n}\n"
    : "+f"(d[0]),"+f"(d[1]),"+f"(d[2]),"+f"(d[3]),"+f"(d[4]),"+f"(d[5]),"+f"(d[6]),"+f"(d[7]),"+f"(d[8]),"+f"(d[9]),"+f"(d[10]),"+f"(d[11]),"+f"(d[12]),"+f"(d[13]),"+f"(d[14]),"+f"(d[15]),"+f"(d[16]),"+f"(d[17]),"+f"(d[18]),"+f"(d[19]),"+f"(d[20]),"+f"(d[21]),"+f"(d[22]),"+f"(d[23]),"+f"(d[24]),"+f"(d[25]),"+f"(d[26]),"+f"(d[27]),"+f"(d[28]),"+f"(d[29]),"+f"(d[30]),"+f"(d[31]),"+f"(d[32]),"+f"(d[33]),"+f"(d[34]),"+f"(d[35]),"+f"(d[36]),"+f"(d[37]),"+f"(d[38]),"+f"(d[39]),"+f"(d[40]),"+f"(d[41]),"+f"(d[42]),"+f"(d[43]),"+f"(d[44]),"+f"(d[45]),"+f"(d[46]),"+f"(d[47]),"+f"(d[48]),"+f"(d[49]),"+f"(d[50]),"+f"(d[51]),"+f"(d[52]),"+f"(d[53]),"+f"(d[54]),"+f"(d[55]),"+f"(d[56]),"+f"(d[57]),"+f"(d[58]),"+f"(d[59]),"+f"(d[60]),"+f"(d[61]),"+f"(d[62]),"+f"(d[63])
    : "l"(descA), "l"(descB), "r"(scaleD));
}
__device__ __forceinline__ void wgmma_ss_n40(float* d, uint64_t descA, uint64_t descB, int scaleD) {
  asm volatile("{\n.reg .pred p;\nsetp.ne.b32 p, %22, 0;\n"
    "wgmma.mma_async.sync.aligned.m64n40k16.f32.bf16.bf16 {%0,%1,%2,%3,%4,%5,%6,%7,%8,%9,%10,%11,%12,%13,%14,%15,%16,%17,%18,%19}, %20, %21, p, 1, 1, 0, 0;\n}\n"
    : "+f"(d[0]),"+f"(d[1]),"+f"(d[2]),"+f"(d[3]),"+f"(d[4]),"+f"(d[5]),"+f"(d[6]),"+f"(d[7]),"+f"(d[8]),"+f"(d[9]),"+f"(d[10]),"+f"(d[11]),"+f"(d[12]),"+f"(d[13]),"+f"(d[14]),"+f"(d[15]),"+f"(d[16]),"+f"(d[17]),"+f"(d[18]),"+f"(d[19])
    : "l"(descA), "l"(descB), "r"(scaleD));
}
__device__ __forceinline__ void wgmma_ss_n32_ta(float* d, uint64_t descA, uint64_t descB, int scaleD) {
  asm volatile("{\n.reg .pred p;\nsetp.ne.b32 p, %18, 0;\n"
    "wgmma.mma_async.sync.aligned.m64n32k16.f32.bf16.bf16 {%0,%1,%2,%3,%4,%5,%6,%7,%8,%9,%10,%11,%12,%13,%14,%15}, %16, %17, p, 1, 1, 1, 0;\n}\n"
    : "+f"(d[0]),"+f"(d[1]),"+f"(d[2]),"+f"(d[3]),"+f"(d[4]),"+f"(d[5]),"+f"(d[6]),"+f"(d[7]),"+f"(d[8]),"+f"(d[9]),"+f"(d[10]),"+f"(d[11]),"+f"(d[12]),"+f"(d[13]),"+f"(d[14]),"+f"(d[15])
    : "l"(descA), "l"(descB), "r"(scaleD));
}
struct ChainArgs {
  const bf16* mem0;
  uint32_t* Mg;
  float4* Sg;
  uint32_t* flag;
  uint32_t* dbg;
};

constexpr int XT_BYTES = 28672;
constexpr int STG_BYTES = 5120;
constexpr int OFF_A = 0, OFF_B = 65536, OFF_C = OFF_B + 3 * XT_BYTES, OFF_M = OFF_C + 2 * XT_BYTES, OFF_P = OFF_M + 2 * 7168,
              OFF_SX = OFF_P + 4096, OFF_SM = OFF_SX + 2048, OFF_SW = OFF_SM + 512, OFF_BAR = OFF_SW + 1024, OFF_DBG = OFF_B + 2 * XT_BYTES + 3 * 7168, SMEM_CHAIN = OFF_BAR + 512;
enum { B_PA = 0, B_PE = 1, B_XF = 4, B_MB = 9, B_SX = 11, B_SM = 13, B_PB = 15, B_KR = 17, B_ST = 21, B_PF = 29, B_RD = 45, B_MF = 47, B_EM = 51, B_SB = 55, B_PE5 = 56, B_NUM = 61 };
#define MD0 250
#define MDELTA 900
#define SSTART 800
#define SXSTART 500
#define SSTAG 130
constexpr float L2E = 1.4426950408889634f;
constexpr int CHAIN_THREADS = 512;
#define TOKK 28

__device__ __forceinline__ uint32_t xstage_off(int st) { return st < 2 ? OFF_C + st * XT_BYTES : OFF_B + (st - 2) * XT_BYTES; }
__device__ __forceinline__ uint32_t mslot_off(int k) { return k < 3 ? OFF_B + 2 * XT_BYTES + k * 7168 : OFF_M; }
constexpr int OFF_VAR = OFF_BAR + 496;

__device__ __forceinline__ bool slot_has_sentinel(const uint8_t* p, int lane) {
  bool bad = false;
#pragma unroll 2
  for (int i = 0; i < 14; i++) { const uint4 v = *reinterpret_cast<const uint4*>(p + (32 * i + lane) * 16); bad |= (v.x == ~0u) | (v.y == ~0u) | (v.z == ~0u) | (v.w == ~0u); }
  return __any_sync(~0u, bad);
}
__device__ __forceinline__ uint32_t clk32() { uint32_t c; asm volatile("mov.u32 %0, %%clock;" : "=r"(c)); return c; }
__device__ __forceinline__ void wait_until(uint32_t t, uint32_t saddr) {
  while ((int)(clk32() - t) < 0) { uint32_t d; asm volatile("ld.volatile.shared.u32 %0, [%1];" : "=r"(d) : "r"(saddr) : "memory"); asm volatile("" ::"r"(d)); if (d == 0x12345u) break; }
}
#define DBG(slot) do {} while (0)
#define DBGV(slot, v) do {} while (0)

#define PDBG(i) do {} while (0)

template <bool CL>
__device__ __forceinline__ void issue_x_load(uint32_t sb, const CUtensorMap* tm_x, const CUtensorMap* tm_x3, int seg, int rank) {
  const int st = seg & 3;
  const uint32_t bar = sb + OFF_BAR + (B_XF + st) * 8;
  const uint32_t dst = sb + xstage_off(st);
  mbar_expect_tx(bar, XT_BYTES);
  if (CL) {
    if (rank < NJ) tma_load_2d_mc(dst + rank * 4096, tm_x, rank * 64, seg * SEG, bar, (uint16_t)0xFFFF);
  } else {
    tma_load_3d(dst, tm_x3, 0, seg * SEG, 0, bar);
  }
}

template <int WG>
__device__ __forceinline__ void tile_prologue(uint32_t* W, uint32_t sb) {
  const uint32_t bar = sb + OFF_BAR;
  const int lane = threadIdx.x & 31;
  float acc[112];
  mbar_wait(bar + B_PA * 8, 0);
#pragma unroll
  for (int half = 0; half < 2; half++) {
#pragma unroll
    for (int ec = 0; ec < 4; ec++) {
      const int i = half * 8 + ec * 2 + WG;
      const int st = i % 5;
      mbar_wait(bar + (B_PF + i) * 8, 0);
      const uint32_t bb = sb + OFF_B + st * XT_BYTES;
      wg_fence();
#pragma unroll
      for (int kk = 0; kk < 4; kk++) {
        if (WG == 0) {
          wgmma_ss_n112(acc, desc_sw128(sb + OFF_A + ec * 8192 + kk * 32), desc_sw128(bb + kk * 32), (ec | kk) != 0);
          wgmma_ss_n112(acc + 56, desc_sw128(sb + OFF_A + ec * 8192 + kk * 32), desc_sw128(bb + 14336 + kk * 32), (ec | kk) != 0);
        } else {
          wgmma_ss_n112_ta(acc, desc_sw128(sb + OFF_A + 32768 + (ec * 64 + kk * 16) * 128), desc_sw128(bb + kk * 32), (ec | kk) != 0);
          wgmma_ss_n112_ta(acc + 56, desc_sw128(sb + OFF_A + 32768 + (ec * 64 + kk * 16) * 128), desc_sw128(bb + 14336 + kk * 32), (ec | kk) != 0);
        }
      }
      wg_commit();
      wg_wait<0>();
      if (lane == 0) mbar_arrive(bar + (B_PE5 + st) * 8);
    }
    const float sc = WG == 0 ? 0.0625f : 1.0f;
#pragma unroll
    for (int kk = 0; kk < 14; kk++) {
      W[half * 56 + kk * 4 + 0] = pack_bf16(acc[8 * kk + 0] * sc, acc[8 * kk + 1] * sc);
      W[half * 56 + kk * 4 + 1] = pack_bf16(acc[8 * kk + 2] * sc, acc[8 * kk + 3] * sc);
      W[half * 56 + kk * 4 + 2] = pack_bf16(acc[8 * kk + 4] * sc, acc[8 * kk + 5] * sc);
      W[half * 56 + kk * 4 + 3] = pack_bf16(acc[8 * kk + 6] * sc, acc[8 * kk + 7] * sc);
    }
  }
}

__device__ __forceinline__ void token_gemm(const uint32_t* W, uint32_t sb, int seg, uint32_t stg_base, int w, int lane) {
  const int st = seg & 3;
  mbar_wait(sb + OFF_BAR + (B_XF + st) * 8, (seg >> 2) & 1);
  const uint32_t xb = sb + xstage_off(st);
  float d[16];
  wg_fence();
#pragma unroll
  for (int kk = 0; kk < TOKK; kk++) wgmma_rs_n32(d, &W[4 * kk], desc_sw128(xb + (kk >> 2) * 4096 + (kk & 3) * 32), kk != 0);
  wg_commit();
  wg_wait<0>();
  const uint32_t stg = stg_base + (seg & 3) * STG_BYTES + 1024;
  const int r = lane & 7, mi = lane >> 3;
#pragma unroll
  for (int p = 0; p < 2; p++) {
    const int t = 8 * (2 * p + (mi >> 1)) + r;
    const int chunk = 2 * w + (mi & 1);
    const uint32_t addr = stg + t * 128 + ((chunk ^ r) << 4);
    stsm_x4_t(addr, pack_bf16(d[8 * p + 0], d[8 * p + 1]), pack_bf16(d[8 * p + 2], d[8 * p + 3]), pack_bf16(d[8 * p + 4], d[8 * p + 5]),
              pack_bf16(d[8 * p + 6], d[8 * p + 7]));
  }
}

__device__ __forceinline__ void poll_smm(uint8_t* smem, uint32_t bar, const float4* src, int s, int p, int lane) {
  volatile uint32_t* var = reinterpret_cast<volatile uint32_t*>(smem + OFF_VAR);
  { int it = 0; while (var[1] != (uint32_t)s && ++it < SPIN_LIMIT) __nanosleep(20); }
  const uint32_t tM = clk32();
  wait_until(tM + SSTART + p * SSTAG, bar - OFF_BAR + OFF_VAR + 12);
  uint4 v; int it = 0; bool mine = true;
  while (true) {
    v = ld_vol_v4(src);
    if (__all_sync(~0u, __uint_as_float(v.z) == 7.f)) break;
    if (mbar_test(bar + (B_SM + (s & 1)) * 8, (s >> 1) & 1)) { mine = false; break; }
    if (++it > SPIN_LIMIT) break;
  }
  if (mine) {
    reinterpret_cast<float2*>(smem + OFF_SM + (s & 1) * 256)[lane] = make_float2(__uint_as_float(v.x), __uint_as_float(v.y));
    __syncwarp();
    if (lane == 0) { if (atomicExch(reinterpret_cast<uint32_t*>(smem + OFF_VAR), (uint32_t)(s + 1)) != (uint32_t)(s + 1)) mbar_arrive(bar + (B_SM + (s & 1)) * 8); }
  }
}

template <bool CL>
__global__ void __launch_bounds__(CHAIN_THREADS, 1)
chain_kernel(const __grid_constant__ CUtensorMap tm_x, const __grid_constant__ CUtensorMap tm_wq, const __grid_constant__ CUtensorMap tm_wk,
             const __grid_constant__ CUtensorMap tm_wv, const __grid_constant__ CUtensorMap tm_wo, const __grid_constant__ CUtensorMap tm_k,
             const __grid_constant__ CUtensorMap tm_y, const __grid_constant__ CUtensorMap tm_x3, ChainArgs args) {
  extern __shared__ __align__(1024) uint8_t smem[];
  const uint32_t sb = smem_u32(smem);
  const int tid = threadIdx.x, warp = tid >> 5, lane = tid & 31;
  const int j = blockIdx.x >> 4, h = blockIdx.x & 15;
  const uint32_t bar = sb + OFF_BAR;
  const int g = lane >> 2, q = lane & 3;
  KT_START(0);

  if (tid == 0) {
    mbar_init(bar + B_PA * 8, 1);
    for (int i = 0; i < 5; i++) mbar_init(bar + (B_PE5 + i) * 8, 4);
    for (int i = 0; i < 16; i++) mbar_init(bar + (B_PF + i) * 8, 1);
    for (int i = 0; i < 5; i++) mbar_init(bar + (B_XF + i) * 8, 1);
    for (int i = 0; i < 2; i++) {
      mbar_init(bar + (B_SX + i) * 8, 4); mbar_init(bar + (B_SM + i) * 8, 1); mbar_init(bar + (B_PB + i) * 8, 1); mbar_init(bar + (B_RD + i) * 8, 1);
    }
    for (int i = 0; i < 4; i++) { mbar_init(bar + (B_KR + i) * 8, 4); mbar_init(bar + (B_MF + i) * 8, 1); mbar_init(bar + (B_EM + i) * 8, 4); }
    mbar_init(bar + B_SB * 8, 1);
    for (int i = 0; i < 8; i++) mbar_init(bar + (B_ST + i) * 8, 4);
    asm volatile("fence.mbarrier_init.release.cluster;" ::: "memory");
  }
  __syncthreads();
  if (CL) cluster_sync_all();
  asm volatile("griddepcontrol.launch_dependents;" ::: "memory");
  PDBG(0);

  const int wgi = __shfl_sync(0xffffffffu, tid >> 7, 0);
  if (wgi < 2) {
    asm volatile("setmaxnreg.inc.sync.aligned.u32 200;");
    const int wg = wgi, w = warp & 3;
    uint32_t W[112];
    mbar_wait(bar + B_PA * 8, 0);
    PDBG(1);
    mbar_wait(bar + B_PF * 8, 0);
    PDBG(2);
    if (wg == 0) tile_prologue<0>(W, sb); else tile_prologue<1>(W, sb);
    PDBG(3);
    named_bar(0, CHAIN_THREADS);
    PDBG(4);
    PDBG(5);

    const uint32_t stg_base = sb + OFF_A + wg * 4 * STG_BYTES;
    token_gemm(W, sb, 0, stg_base, w, lane);
    PDBG(6);
    PDBG(7);
    __syncwarp();
    if (wg == 0 && lane == 0) mbar_arrive(bar + (B_KR + 0) * 8);

    if (wg == 0) {
      for (int s = 0; s < NSEG; s++) {
        float d0, d1, d2, d3;
        uint32_t ma[2];
        volatile uint32_t* var = reinterpret_cast<volatile uint32_t*>(smem + OFF_VAR);
        mbar_wait(bar + B_SB * 8, s & 1);
        uint32_t n = var[3];
        const uint32_t n_first = n;
        while (true) {
          const int slot = n & 3;
          mbar_wait(bar + (B_MF + slot) * 8, (n >> 2) & 1);
          if (tid == 0) DBG(0);
          const uint32_t ms = sb + mslot_off(slot);
          float a4[4][4];
#pragma unroll
          for (int i = 0; i < 4; i++) { a4[i][0] = a4[i][1] = a4[i][2] = a4[i][3] = 0.f; }
          uint32_t b[14][4];
#pragma unroll
          for (int i = 0; i < 14; i++) ldsm_x4_t(b[i], ms + (32 * i + lane) * 16);
          ldsm_x2_t(ma, ms + (64 * j + 16 * w + (lane & 15)) * 16);
#pragma unroll
          for (int i = 0; i < 14; i++) {
            mma16816(a4[(2 * i) & 3], W[8 * i + 0], W[8 * i + 1], W[8 * i + 2], W[8 * i + 3], b[i][0], b[i][1]);
            mma16816(a4[(2 * i + 1) & 3], W[8 * i + 4], W[8 * i + 5], W[8 * i + 6], W[8 * i + 7], b[i][2], b[i][3]);
          }
          d0 = (a4[0][0] + a4[1][0]) + (a4[2][0] + a4[3][0]); d1 = (a4[0][1] + a4[1][1]) + (a4[2][1] + a4[3][1]);
          d2 = (a4[0][2] + a4[1][2]) + (a4[2][2] + a4[3][2]); d3 = (a4[0][3] + a4[1][3]) + (a4[2][3] + a4[3][3]);
          if (!__any_sync(~0u, (d0 != d0) | (d1 != d1))) break;
          if (!slot_has_sentinel(smem + mslot_off(slot), lane)) break;
          if (n - n_first > (uint32_t)SPIN_LIMIT) break;
          if (lane == 0) mbar_arrive(bar + (B_EM + slot) * 8);
          n++;
        }
        if (tid == 0) { var[2] = n; var[1] = s; DBGV(14, n - n_first); }
        asm volatile("bar.arrive 5, 256;" ::: "memory");
        if (tid == 0) { asm volatile("" :: "f"(d0), "f"(d3)); DBG(8); }
        const uint32_t kb0 = movm_t(pack_bf16(d0, d1)), kb1 = movm_t(pack_bf16(d2, d3));
        if (s < NSEG - 1) {
          float c[4] = {0.f, 0.f, 0.f, 0.f};
          mma16816(c, ma[0], 0u, ma[1], 0u, kb0, kb1);
          float2* sw = reinterpret_cast<float2*>(smem + OFF_SW);
          sw[w * 32 + lane] = make_float2(c[0], c[1]);
          if (tid == 0) DBG(9);
          named_bar(1, 128);
          if (tid == 0) DBG(10);
          if (w == 0) {
            const float2 v0 = sw[lane], v1 = sw[32 + lane], v2 = sw[64 + lane], v3 = sw[96 + lane];
            red_v4(args.Sg + (((size_t)s * NH + h) * 5 + 4) * 32 + lane, (v0.x + v1.x) + (v2.x + v3.x), (v0.y + v1.y) + (v2.y + v3.y), 1.f, 0.f);
          }
        }
        asm volatile("bar.arrive 3, 256;" ::: "memory");
        if (tid == 0) DBG(1);
        {
          const uint32_t stg = stg_base + (s & 3) * STG_BYTES + g * 128 + q * 4;
          asm volatile("st.shared.u32 [%0], %1;" ::"r"(stg + (((2 * w) ^ g) << 4)), "r"(kb0) : "memory");
          asm volatile("st.shared.u32 [%0], %1;" ::"r"(stg + (((2 * w + 1) ^ g) << 4)), "r"(kb1) : "memory");
          fence_async_smem();
          __syncwarp();
          if (lane == 0) mbar_arrive(bar + (B_ST + (s & 3)) * 8);
        }
        if (s + 1 < NSEG) {
          token_gemm(W, sb, s + 1, stg_base, w, lane);
          __syncwarp();
          if (lane == 0) mbar_arrive(bar + (B_KR + ((s + 1) & 3)) * 8);
        }
        if (tid == 0) DBG(11);
        named_bar(1, 128);
      }
    } else {
      const int hd = w * 4 + (lane >> 3);
      uint32_t p_dst = sb + OFF_P + h * 128 + (lane & 7) * 16, p_bar = bar + B_PB * 8;
      if (CL) { p_dst = mapa(p_dst, hd); p_bar = mapa(p_bar, hd); }
      const uint32_t ONE2 = 0x3F803F80u;
      for (int s = 0; s < NSEG; s++) {
        if (s < NSEG - 1) {
          mbar_wait(bar + (B_KR + (s & 3)) * 8, (s >> 2) & 1);
          const uint32_t kst = sb + OFF_A + (s & 3) * STG_BYTES + 1024;
          uint32_t bk[2][4];
#pragma unroll
          for (int i = 0; i < 2; i++) ldsm_x4(bk[i], kst + (8 * w + (lane & 7)) * 128 + (((4 * i + (lane >> 3)) ^ (lane & 7)) << 4));
          float c[4], c2[4];
          volatile uint32_t* var = reinterpret_cast<volatile uint32_t*>(smem + OFF_VAR);
          mbar_wait(bar + B_SB * 8, s & 1);
          uint32_t n = var[3];
          mbar_wait(bar + (B_MF + (n & 3)) * 8, (n >> 2) & 1);
          bool synced = false;
          while (true) {
            const uint32_t ms = sb + mslot_off(n & 3);
            c[0] = c[1] = c[2] = c[3] = 0.f; c2[0] = c2[1] = c2[2] = c2[3] = 0.f;
            uint32_t a[2][4];
            ldsm_x4_t(a[0], ms + (64 * j + lane) * 16);
            ldsm_x4_t(a[1], ms + (64 * j + 32 + lane) * 16);
            mma16816(c, a[0][0], 0u, a[0][1], 0u, bk[0][0], bk[0][1]);
            mma16816(c2, a[0][2], 0u, a[0][3], 0u, bk[0][2], bk[0][3]);
            mma16816(c, a[1][0], 0u, a[1][1], 0u, bk[1][0], bk[1][1]);
            mma16816(c2, a[1][2], 0u, a[1][3], 0u, bk[1][2], bk[1][3]);
            c[0] += c2[0]; c[1] += c2[1];
            if (synced || !__any_sync(~0u, (c[0] != c[0]) | (c[1] != c[1]))) break;
            named_bar(5, 256);
            synced = true;
            n = var[2];
          }
          red_v4(args.Sg + (((size_t)s * NH + h) * 5 + w) * 32 + lane, c[0], c[1], 1.f, 0.f);
          if (!synced) named_bar(5, 256);
        } else named_bar(5, 256);
        named_bar(3, 256);
        const uint32_t ms = sb + mslot_off(reinterpret_cast<volatile uint32_t*>(smem + OFF_VAR)[2] & 3);
        float a4[4][4];
#pragma unroll
        for (int i = 0; i < 4; i++) { a4[i][0] = a4[i][1] = a4[i][2] = a4[i][3] = 0.f; }
        {
          uint32_t b[14][4];
#pragma unroll
          for (int i = 0; i < 14; i++) ldsm_x4_t(b[i], ms + (32 * i + lane) * 16);
#pragma unroll
          for (int i = 0; i < 14; i++) {
            mma16816(a4[(2 * i) & 3], W[8 * i + 0], W[8 * i + 1], W[8 * i + 2], W[8 * i + 3], b[i][0], b[i][1]);
            mma16816(a4[(2 * i + 1) & 3], W[8 * i + 4], W[8 * i + 5], W[8 * i + 6], W[8 * i + 7], b[i][2], b[i][3]);
          }
        }
        const uint32_t za0 = pack_bf16((a4[0][0] + a4[1][0]) + (a4[2][0] + a4[3][0]), (a4[0][1] + a4[1][1]) + (a4[2][1] + a4[3][1]));
        const uint32_t za1 = pack_bf16((a4[0][2] + a4[1][2]) + (a4[2][2] + a4[3][2]), (a4[0][3] + a4[1][3]) + (a4[2][3] + a4[3][3]));
        {
          const uint32_t stg = stg_base + (s & 3) * STG_BYTES + g * 128 + q * 4;
          asm volatile("st.shared.u32 [%0], %1;" ::"r"(stg + (((2 * w) ^ g) << 4)), "r"(movm_t(za0)) : "memory");
          asm volatile("st.shared.u32 [%0], %1;" ::"r"(stg + (((2 * w + 1) ^ g) << 4)), "r"(movm_t(za1)) : "memory");
          fence_async_smem();
          __syncwarp();
          if (lane == 0) mbar_arrive(bar + (B_ST + 4 + (s & 3)) * 8);
        }
        if (s < NSEG - 1) {
          uint32_t va[2][4];
          const uint32_t vst = stg_base + (s & 3) * STG_BYTES + 1024;
#pragma unroll
          for (int kk = 0; kk < 2; kk++) {
            const int mi = lane >> 3, r = lane & 7;
            const int t = 8 * (2 * kk + (mi >> 1)) + r;
            ldsm_x4_t(va[kk], vst + t * 128 + (((2 * w + (mi & 1)) ^ r) << 4));
          }
          mbar_wait(bar + (B_SX + (s & 1)) * 8, (s >> 1) & 1);
          const float2* sx = reinterpret_cast<const float2*>(smem + OFF_SX + (s & 1) * 1024);
          float ex[8];
#pragma unroll
          for (int nt = 0; nt < 4; nt++) { const float2 v = sx[nt * 32 + lane]; ex[2 * nt] = v.x; ex[2 * nt + 1] = v.y; }
          float mx = fmaxf(fmaxf(fmaxf(ex[0], ex[1]), fmaxf(ex[2], ex[3])), fmaxf(fmaxf(ex[4], ex[5]), fmaxf(ex[6], ex[7])));
          mx = fmaxf(mx, __shfl_xor_sync(~0u, mx, 1));
          mx = fmaxf(mx, __shfl_xor_sync(~0u, mx, 2));
#pragma unroll
          for (int k = 0; k < 8; k++) ex[k] = ex2((ex[k] - mx) * L2E);
          mbar_wait(bar + (B_SM + (s & 1)) * 8, (s >> 1) & 1);
          if (tid == 128) DBG(2);
          const float2 sm = reinterpret_cast<const float2*>(smem + OFF_SM + (s & 1) * 256)[lane];
          float mm = fmaxf(sm.x, sm.y);
          mm = fmaxf(mm, __shfl_xor_sync(~0u, mm, 1));
          mm = fmaxf(mm, __shfl_xor_sync(~0u, mm, 2));
          const float m = fmaxf(mx, mm);
          const float f = ex2((mx - m) * L2E);
          const uint32_t pm = pack_bf16(ex2((sm.x - m) * L2E), ex2((sm.y - m) * L2E));
          uint32_t bx[4];
#pragma unroll
          for (int nt = 0; nt < 4; nt++) bx[nt] = pack_bf16(ex[2 * nt] * f, ex[2 * nt + 1] * f);
          float o0[4] = {0.f, 0.f, 0.f, 0.f}, o1[4] = {0.f, 0.f, 0.f, 0.f}, o2[4] = {0.f, 0.f, 0.f, 0.f};
          float l0[4] = {0.f, 0.f, 0.f, 0.f}, l1[4] = {0.f, 0.f, 0.f, 0.f}, l2[4] = {0.f, 0.f, 0.f, 0.f};
          mma1688(o0, za0, za1, pm);
          mma1688(l0, ONE2, ONE2, pm);
          mma16816(o1, va[0][0], va[0][1], va[0][2], va[0][3], bx[0], bx[1]);
          mma16816(l1, ONE2, ONE2, ONE2, ONE2, bx[0], bx[1]);
          mma16816(o2, va[1][0], va[1][1], va[1][2], va[1][3], bx[2], bx[3]);
          mma16816(l2, ONE2, ONE2, ONE2, ONE2, bx[2], bx[3]);
          const float r0 = __fdividef(1.f, l0[0] + l1[0] + l2[0]), r1 = __fdividef(1.f, l0[1] + l1[1] + l2[1]);
          const float v0 = (o0[0] + o1[0] + o2[0]) * r0, v1 = (o0[1] + o1[1] + o2[1]) * r1;
          const float v2 = (o0[2] + o1[2] + o2[2]) * r0, v3 = (o0[3] + o1[3] + o2[3]) * r1;
          if (CL) {
            st_async_v4(p_dst + (s & 1) * 2048, v0, v1, v2, v3, p_bar + (s & 1) * 8);
          } else {
            uint4* dst = reinterpret_cast<uint4*>(args.Sg + (size_t)NSEG * NH * 5 * 32) + ((((size_t)s * NJ + j) * 16 + hd) * 16 + h) * 8 + (lane & 7);
            uint32_t u0 = ~__float_as_uint(v0), u1 = ~__float_as_uint(v1), u2 = ~__float_as_uint(v2), u3 = ~__float_as_uint(v3);
            u0 += (u0 == 0); u1 += (u1 == 0); u2 += (u2 == 0); u3 += (u3 == 0);
            asm volatile("st.relaxed.gpu.global.v4.u32 [%0], {%1,%2,%3,%4};" ::"l"(dst), "r"(u0), "r"(u1), "r"(u2), "r"(u3) : "memory");
          }
          if (tid == 128) DBG(3);
        }
        if (s + 1 < NSEG) token_gemm(W, sb, s + 1, stg_base, w, lane);
        if (tid == 128) DBG(12);
      }
    }
  } else if (wgi == 2) {
    asm volatile("setmaxnreg.dec.sync.aligned.u32 80;");
    const int aw = warp - 8, at = tid - 256;
    named_bar(0, CHAIN_THREADS);
    for (int s = 0; s < NSEG; s++) {
      volatile uint32_t* var = reinterpret_cast<volatile uint32_t*>(smem + OFF_VAR);
      if (s == 0) {
        for (int c = at; c < DM; c += 128) {
          uint32_t v[4];
#pragma unroll
          for (int i = 0; i < 4; i++) {
            uint32_t lo = reinterpret_cast<const uint16_t*>(args.mem0)[(2 * i) * DM + c], hi = reinterpret_cast<const uint16_t*>(args.mem0)[(2 * i + 1) * DM + c];
            if (lo == 0xFFFFu) lo = 0x7FFFu;
            if (hi == 0xFFFFu) hi = 0x7FFFu;
            v[i] = lo | (hi << 16);
          }
          *reinterpret_cast<uint4*>(smem + mslot_off(0) + c * 16) = make_uint4(v[0], v[1], v[2], v[3]);
        }
        fence_async_smem();
        named_bar(2, 128);
        if (at == 0) mbar_arrive(bar + B_MF * 8);
      }
      { int it = 0; while (var[1] != (uint32_t)s && ++it < SPIN_LIMIT) __nanosleep(20); }
      if (j == 0) {
        const float4 z4 = make_float4(0.f, 0.f, 0.f, 0.f);
        if (s >= 2) { float4* p = args.Sg + ((size_t)(s - 2) * NH + h) * 160; p[aw * 32 + lane] = z4; if (aw == 0) p[128 + lane] = z4; }
        if (s == NSEG - 1) { float4* p = args.Sg + ((size_t)(s - 1) * NH + h) * 160; p[aw * 32 + lane] = z4; if (aw == 0) p[128 + lane] = z4; }
      }
      if (at == 32) DBG(4);
      if (s == NSEG - 1) break;
      const uint32_t tM = clk32();
      {
        const float4* src = args.Sg + (((size_t)s * NH + h) * 5 + aw) * 32 + lane;
        wait_until(tM + SXSTART, sb + OFF_VAR + 12);
        uint4 v; int it = 0;
        do { v = ld_vol_v4(src); } while (__uint_as_float(v.z) != 7.f && ++it < SPIN_LIMIT);
        reinterpret_cast<float2*>(smem + OFF_SX + (s & 1) * 1024)[aw * 32 + lane] = make_float2(__uint_as_float(v.x), __uint_as_float(v.y));
        __syncwarp();
        if (lane == 0) mbar_arrive(bar + (B_SX + (s & 1)) * 8);
        if (at == 0) DBG(13);
      }
    }
  } else {
    asm volatile("setmaxnreg.dec.sync.aligned.u32 32;");
    if (tid == 384) {
      reinterpret_cast<uint32_t*>(smem + OFF_VAR)[0] = 0; reinterpret_cast<uint32_t*>(smem + OFF_VAR)[1] = ~0u;
      mbar_expect_tx(bar + B_PA * 8, 65536);
#pragma unroll
      for (int ec = 0; ec < 4; ec++) tma_load_2d(sb + OFF_A + ec * 8192, &tm_wq, h * DH + ec * 64, 64 * j, bar + B_PA * 8);
      tma_load_2d(sb + OFF_A + 32768, &tm_wo, 64 * j, h * DH, bar + B_PA * 8);
      for (int i = 0; i < 16; i++) {
        const int st = i % 5, half = i >> 3, ec = (i & 7) >> 1;
        if (i >= 5) mbar_wait(bar + (B_PE5 + st) * 8, ((i / 5) - 1) & 1);
        mbar_expect_tx(bar + (B_PF + i) * 8, XT_BYTES);
        tma_load_2d(sb + OFF_B + st * XT_BYTES, (i & 1) ? &tm_wv : &tm_wk, h * DH + ec * 64, half * 224, bar + (B_PF + i) * 8);
      }
    }
    if (tid == 384) {
#pragma unroll 1
      for (int sg = 0; sg < 2; sg++) {
        mbar_wait(bar + (B_PE5 + 3 + sg) * 8, 0);
        mbar_expect_tx(bar + (B_XF + sg) * 8, XT_BYTES);
        tma_load_3d(sb + xstage_off(sg), &tm_x3, 0, sg * SEG, 0, bar + (B_XF + sg) * 8);
      }
    }
    if (warp == 13 && !(lane & 1)) {
      const int l8 = lane >> 2, v = lane & 3;
      const int c = 16 * (h >> 2) + 2 * (h & 3) + (l8 >> 2) + (v >> 1) * 8;
      for (int s = 1; s < NSEG; s++) st_relaxed(args.Mg + (size_t)s * 1792 + (64 * j + c) * 4 + (l8 & 3), 0xFFFFFFFFu);
      __threadfence();
    }
    __syncwarp();
    named_bar(0, CHAIN_THREADS);
    if (tid == 384) {
      issue_x_load<false>(sb, &tm_x, &tm_x3, 2, h);
      for (int s = 0; s < NSEG; s++) {
        mbar_wait(bar + (B_ST + (s & 3)) * 8, (s >> 2) & 1);
        tma_store_2d(&tm_k, 64 * j, (h * NSEG + s) * LKEY, sb + OFF_A + (s & 3) * STG_BYTES);
        mbar_wait(bar + (B_ST + 4 + (s & 3)) * 8, (s >> 2) & 1);
        tma_store_2d(&tm_y, 64 * j, (h * NSEG + s) * LKEY, sb + OFF_A + (4 + (s & 3)) * STG_BYTES);
        bulk_commit();
        if (s + 3 < NSEG) { if (s == 0) issue_x_load<false>(sb, &tm_x, &tm_x3, 3, h); else issue_x_load<CL>(sb, &tm_x, &tm_x3, s + 3, h); }
        bulk_wait<0>();
        fence_async_all();
        __threadfence();
        red_u32(args.flag + s, 1u);
      }
    } else if (warp == 13) {
      for (int s = 0; s < NSEG - 1; s++) {
        float acc;
        if (CL && lane == 0) mbar_expect_tx(bar + (B_PB + (s & 1)) * 8, 16 * 128);
        poll_smm(smem, bar, args.Sg + (((size_t)s * NH + h) * 5 + 4) * 32 + lane, s, 1, lane);
        if (CL) {
          mbar_wait_cluster(bar + (B_PB + (s & 1)) * 8, (s >> 1) & 1);
          if (lane == 0) DBG(5);
          const float* pin = reinterpret_cast<const float*>(smem + OFF_P + (s & 1) * 2048);
          float a0 = 0.f, a1 = 0.f, a2 = 0.f, a3 = 0.f;
#pragma unroll
          for (int k = 0; k < 16; k += 4) { a0 += pin[k * 32 + lane]; a1 += pin[(k + 1) * 32 + lane]; a2 += pin[(k + 2) * 32 + lane]; a3 += pin[(k + 3) * 32 + lane]; }
          acc = (a0 + a1) + (a2 + a3);
        } else {
          const uint32_t* src = reinterpret_cast<const uint32_t*>(args.Sg + (size_t)NSEG * NH * 5 * 32) + (((size_t)s * NJ + j) * 16 + h) * 16 * 32 + lane;
          acc = 0.f;
#pragma unroll 1
          for (int k = 0; k < 16; k += 4) {
            uint32_t v0, v1, v2, v3; int it = 0;
            do {
              asm volatile("ld.volatile.global.u32 %0, [%1];" : "=r"(v0) : "l"(src + k * 32) : "memory");
              asm volatile("ld.volatile.global.u32 %0, [%1];" : "=r"(v1) : "l"(src + k * 32 + 32) : "memory");
              asm volatile("ld.volatile.global.u32 %0, [%1];" : "=r"(v2) : "l"(src + k * 32 + 64) : "memory");
              asm volatile("ld.volatile.global.u32 %0, [%1];" : "=r"(v3) : "l"(src + k * 32 + 96) : "memory");
            } while ((v0 == 0u || v1 == 0u || v2 == 0u || v3 == 0u) && ++it < SPIN_LIMIT);
            acc += (__uint_as_float(~v0) + __uint_as_float(~v1)) + (__uint_as_float(~v2) + __uint_as_float(~v3));
            uint32_t* cl = const_cast<uint32_t*>(src) + k * 32;
            cl[0] = 0u; cl[32] = 0u; cl[64] = 0u; cl[96] = 0u;
          }
        }
        const float o = __shfl_down_sync(~0u, acc, 1);
        const uint32_t u = pack_bf16(acc, o);
        const int l8 = lane >> 2, v = lane & 3;
        const int c = 16 * (h >> 2) + 2 * (h & 3) + (l8 >> 2) + (v >> 1) * 8;
        if (!(lane & 1)) st_relaxed(args.Mg + (size_t)(s + 1) * 1792 + (64 * j + c) * 4 + (l8 & 3), u);
        if (lane == 0) { DBG(6); mbar_arrive(bar + (B_RD + (s & 1)) * 8); }
      }
    } else if (warp == 15) {
      for (int s = 0; s < NSEG - 1; s++) poll_smm(smem, bar, args.Sg + (((size_t)s * NH + h) * 5 + 4) * 32 + lane, s, 0, lane);
    } else if (tid == 448) {
      volatile uint32_t* var = reinterpret_cast<volatile uint32_t*>(smem + OFF_VAR);
      uint32_t n = 0, empar = 0;
      for (int s = 0; s < NSEG; s++) {
        if (s > 0) mbar_wait(bar + (B_RD + ((s - 1) & 1)) * 8, ((s - 1) >> 1) & 1);
        const uint32_t n0 = n;
        var[3] = n0;
        mbar_arrive(bar + B_SB * 8);
        uint32_t tnext = clk32() + MD0;
        int it = 0;
        if (s == 0) n = 1;
        while (s > 0) {
          bool done = false;
          while ((int)(clk32() - tnext) < 0) { if (var[1] == (uint32_t)s) { done = true; break; } }
          if (done || var[1] == (uint32_t)s || ++it > SPIN_LIMIT) break;
          const int slot = n & 3;
          if (n - n0 >= 4) {
            int it2 = 0;
            while (!mbar_test(bar + (B_EM + slot) * 8, (empar >> slot) & 1)) { if (var[1] == (uint32_t)s || ++it2 > SPIN_LIMIT) { done = true; break; } }
            if (done) break;
            empar ^= 1u << slot;
          }
          mbar_expect_tx(bar + (B_MF + slot) * 8, 7168);
          bulk_load(sb + mslot_off(slot), args.Mg + (size_t)s * 1792, 7168, bar + (B_MF + slot) * 8);
          n++;
          tnext += MDELTA;
        }
        { int it3 = 0; while (var[1] != (uint32_t)s && ++it3 < SPIN_LIMIT) {} }
        const uint32_t ns = var[2];
        const uint32_t waited = n - n0 > 4 ? n - n0 - 4 : 0;
        for (uint32_t a = n0 + waited; a < ns; a++) empar ^= 1u << (a & 3);
        for (uint32_t a = ns + 1; a < n; a++) mbar_wait(bar + (B_MF + (a & 3)) * 8, (a >> 2) & 1);
        DBGV(15, n - n0);
      }
    }
    __syncwarp();
  }
  named_bar(0, CHAIN_THREADS);
  KT_END(0);
  if (CL) cluster_sync_all();
}
struct SsmArgs {
  const bf16 *lam_re, *lam_im, *log_dt, *dskip, *x, *gate_w;
  float* hloc;
  float2* hend;
  float* omg;
  float* gate;
  float4* tab;
  float* out;
};

__device__ __forceinline__ float bf2f(bf16 v) { return __bfloat162float(v); }
__device__ __forceinline__ float rbf(float v) { return __bfloat162float(__float2bfloat16_rn(v)); }
__device__ __forceinline__ float2 cmul(float2 a, float2 b) { return make_float2(a.x * b.x - a.y * b.y, a.x * b.y + a.y * b.x); }
__device__ __forceinline__ float2 ssm_z(const SsmArgs& a, int ch) {
  const float dt = rbf(expf(bf2f(a.log_dt[ch])));
  return make_float2(dt * bf2f(a.lam_re[ch]), dt * bf2f(a.lam_im[ch]));
}
__device__ __forceinline__ float2 cexp_n(float2 z, float n) {
  float sn, cs;
  sincosf(z.y * n, &sn, &cs);
  const float e = expf(z.x * n);
  return make_float2(e * cs, e * sn);
}

__global__ void __launch_bounds__(128) gate_kernel(SsmArgs args) {
  const int warp = threadIdx.x >> 5, lane = threadIdx.x & 31;
  const int t0 = blockIdx.x * 32 + warp * 8;
  float acc[8];
#pragma unroll
  for (int tt = 0; tt < 8; tt++) acc[tt] = 0.f;
#pragma unroll
  for (int d = 2 * lane; d < DM; d += 64) {
    const __nv_bfloat162 wv = *reinterpret_cast<const __nv_bfloat162*>(args.gate_w + d);
#pragma unroll
    for (int tt = 0; tt < 8; tt++) {
      const __nv_bfloat162 xv = *reinterpret_cast<const __nv_bfloat162*>(args.x + (size_t)(t0 + tt) * DM + d);
      acc[tt] += rbf(bf2f(xv.x) * bf2f(wv.x)) + rbf(bf2f(xv.y) * bf2f(wv.y));
    }
  }
#pragma unroll
  for (int tt = 0; tt < 8; tt++) {
#pragma unroll
    for (int o = 16; o; o >>= 1) acc[tt] += __shfl_xor_sync(~0u, acc[tt], o);
    if (lane == 0) {
      const float gv = rbf(1.f / (1.f + expf(-rbf(acc[tt]))));
      args.gate[t0 + tt] = gv;
      args.omg[t0 + tt] = rbf(1.f - gv);
    }
  }
}

constexpr int S1_STAGE = 32768, S1_NST = 3, S1_SMEM = S1_NST * S1_STAGE + 256;
__global__ void __launch_bounds__(160, 2)
ssm1_kernel(const __grid_constant__ CUtensorMap tm_bre, const __grid_constant__ CUtensorMap tm_bim, const __grid_constant__ CUtensorMap tm_xp, SsmArgs args) {
  extern __shared__ __align__(1024) uint8_t smem[];
  const uint32_t sb = smem_u32(smem), bar = sb + S1_NST * S1_STAGE;
  const int tid = threadIdx.x, warp = tid >> 5, lane = tid & 31;
  const int cg = blockIdx.x, tc = blockIdx.y;
  KT_START(1);
  if (tid == 0) {
    for (int i = 0; i < 7; i++) mbar_init(bar + i * 8, 1);
    for (int i = 0; i < 3; i++) mbar_init(bar + (8 + i) * 8, 4);
    asm volatile("fence.mbarrier_init.release.cluster;" ::: "memory");
  }
  __syncthreads();
  if (warp == 4) {
    if (lane == 0) {
      for (int kc = 0; kc < 7; kc++) {
        const int st = kc % 3;
        if (kc >= 3) mbar_wait(bar + (8 + st) * 8, ((kc / 3) - 1) & 1);
        mbar_expect_tx(bar + kc * 8, S1_STAGE);
        tma_load_2d(sb + st * S1_STAGE, &tm_bre, kc * 64, cg * 64, bar + kc * 8);
        tma_load_2d(sb + st * S1_STAGE + 8192, &tm_bim, kc * 64, cg * 64, bar + kc * 8);
        tma_load_4d(sb + st * S1_STAGE + 16384, &tm_xp, kc * 64, 0, tc * 4, 0, bar + kc * 8);
      }
    }
    return;
  }
  const int g = lane >> 2, q = lane & 3;
  float2 zz[2]; float lre[2], lim[2];
#pragma unroll
  for (int r = 0; r < 2; r++) { const int ch = cg * 64 + warp * 16 + g + r * 8; zz[r] = ssm_z(args, ch); lre[r] = bf2f(args.lam_re[ch]); lim[r] = bf2f(args.lam_im[ch]); }
  float ur[64], ui[64];
#pragma unroll 1
  for (int kc = 0; kc < 7; kc++) {
    const int st = kc % 3;
    mbar_wait(bar + kc * 8, 0);
    const uint32_t b0 = sb + st * S1_STAGE;
    wg_fence();
#pragma unroll
    for (int kk = 0; kk < 4; kk++) {
      wgmma_ss_n128(ur, desc_sw128(b0 + kk * 32), desc_sw128(b0 + 16384 + kk * 32), (kc | kk) != 0);
      wgmma_ss_n128(ui, desc_sw128(b0 + 8192 + kk * 32), desc_sw128(b0 + 16384 + kk * 32), (kc | kk) != 0);
    }
    wg_commit();
    wg_wait<0>();
    if (lane == 0) mbar_arrive(bar + (8 + st) * 8);
  }
#pragma unroll
  for (int r = 0; r < 2; r++) {
    const int ch = cg * 64 + warp * 16 + g + r * 8;
    const float2 z = zz[r];
    const float2 lam = cexp_n(z, 1.f);
    const float lr = lre[r], li = lim[r];
    const float den = lr * lr + li * li;
    const float2 num = make_float2(lam.x - 1.f, lam.y);
    const float2 coef = make_float2((num.x * lr + num.y * li) / den, (num.y * lr - num.x * li) / den);
    float2 hs = make_float2(0.f, 0.f);
#pragma unroll
    for (int i = 0; i < 32; i++) {
      const int idx = (i >> 1) * 4 + r * 2 + (i & 1);
      const float2 bu = cmul(coef, make_float2(ur[idx], ui[idx]));
      hs = make_float2(fmaf(lam.x, hs.x, fmaf(-lam.y, hs.y, bu.x)), fmaf(lam.x, hs.y, fmaf(lam.y, hs.x, bu.y)));
      ur[idx] = hs.x; ui[idx] = hs.y;
    }
    const float2 l32 = cexp_n(z, 32.f);
    if (tc == 0 && q == 0) {
      const float2 l128 = cexp_n(z, 128.f);
      args.tab[ch * 2] = make_float4(lam.x, lam.y, l32.x, l32.y);
      args.tab[ch * 2 + 1] = make_float4(l128.x, l128.y, 0.f, 0.f);
    }
    float2 carry = make_float2(0.f, 0.f);
#pragma unroll
    for (int qq = 0; qq < 3; qq++) {
      const float ex = __shfl_sync(~0u, hs.x, (lane & ~3) + qq), ey = __shfl_sync(~0u, hs.y, (lane & ~3) + qq);
      if (qq < q) { const float2 t = cmul(l32, carry); carry = make_float2(t.x + ex, t.y + ey); }
    }
    float2 p = lam;
    float4* dre = reinterpret_cast<float4*>(args.hloc) + ((((size_t)tc * 7 + cg) * 4 + warp) * 2 + r) * 256 + lane;
    float4* dim = dre + (size_t)DM * SEQ / 4;
#pragma unroll
    for (int i4 = 0; i4 < 8; i4++) {
      float vr[4], vi[4];
#pragma unroll
      for (int e = 0; e < 4; e++) {
        const int i = i4 * 4 + e, idx = (i >> 1) * 4 + r * 2 + (i & 1);
        const float2 t = cmul(p, carry);
        vr[e] = ur[idx] + t.x; vi[e] = ui[idx] + t.y;
        p = cmul(p, lam);
      }
      dre[i4 * 32] = make_float4(vr[0], vr[1], vr[2], vr[3]);
      dim[i4 * 32] = make_float4(vi[0], vi[1], vi[2], vi[3]);
      if (i4 == 7 && q == 3) args.hend[tc * DM + ch] = make_float2(vr[3], vi[3]);
    }
  }
  KT_END(1);
}

constexpr int S2_A = 896 * 128, S2_NST = 3, S2_SMEM = S2_A + S2_NST * XT_BYTES + 1024;
__global__ void __launch_bounds__(288, 1)
ssm2_kernel(const __grid_constant__ CUtensorMap tm_cre, const __grid_constant__ CUtensorMap tm_cim, SsmArgs args) {
  extern __shared__ __align__(1024) uint8_t smem[];
  const uint32_t sb = smem_u32(smem), bar = sb + S2_A + S2_NST * XT_BYTES;
  float* sg = reinterpret_cast<float*>(smem + S2_A + S2_NST * XT_BYTES + 512);
  const int tid = threadIdx.x, warp = tid >> 5, lane = tid & 31;
  const int t0 = blockIdx.x * 64, chunk = t0 >> 7, tau0 = t0 & 127;
  KT_START(2);
  if (tid == 0) {
    for (int i = 0; i < 28; i++) mbar_init(bar + i * 8, 1);
    for (int i = 0; i < 3; i++) mbar_init(bar + (28 + i) * 8, 4);
    asm volatile("fence.mbarrier_init.release.cluster;" ::: "memory");
  }
  __syncthreads();
  if (warp == 8) {
    if (lane == 0) {
      for (int i = 0; i < 28; i++) {
        const int st = i % 3, kc = i >> 1;
        if (i >= 3) mbar_wait(bar + (28 + st) * 8, ((i / 3) - 1) & 1);
        mbar_expect_tx(bar + i * 8, XT_BYTES);
        tma_load_2d(sb + S2_A + st * XT_BYTES, kc < 7 ? &tm_cre : &tm_cim, (kc % 7) * 64, (i & 1) * 224, bar + i * 8);
      }
    }
    return;
  }
  if (tid < 64) sg[tid] = args.gate[t0 + tid];
  for (int it = tid; it < DM * 2; it += 256) {
    const int qi = it & 1, gg = (it >> 1) & 7, r = (it >> 4) & 1, cw = it >> 5;
    const int ch = cw * 16 + r * 8 + gg;
    const float4 tb0 = args.tab[ch * 2], tb1 = args.tab[ch * 2 + 1];
    float2 e[15];
#pragma unroll
    for (int c = 0; c < 15; c++) e[c] = c < chunk ? args.hend[c * DM + ch] : make_float2(0.f, 0.f);
    const int qq = (tau0 >> 5) + qi;
    const float4* sre = reinterpret_cast<const float4*>(args.hloc) + (((size_t)chunk * 28 + cw) * 2 + r) * 256 + gg * 4 + qq;
    const float4* sim = sre + (size_t)DM * SEQ / 4;
    float4 vr4[8], vi4[8];
#pragma unroll
    for (int i4 = 0; i4 < 8; i4++) { vr4[i4] = sre[i4 * 32]; vi4[i4] = sim[i4 * 32]; }
    const float2 l128 = make_float2(tb1.x, tb1.y), lam = make_float2(tb0.x, tb0.y), l32 = make_float2(tb0.z, tb0.w);
    float2 hin = make_float2(0.f, 0.f);
#pragma unroll
    for (int c = 0; c < 15; c++) if (c < chunk) { const float2 t = cmul(l128, hin); hin = make_float2(t.x + e[c].x, t.y + e[c].y); }
    float2 p = cmul(lam, hin);
    for (int k = 0; k < qq; k++) p = cmul(p, l32);
#pragma unroll
    for (int m = 0; m < 4; m++) {
      float vr[8] = {vr4[2 * m].x, vr4[2 * m].y, vr4[2 * m].z, vr4[2 * m].w, vr4[2 * m + 1].x, vr4[2 * m + 1].y, vr4[2 * m + 1].z, vr4[2 * m + 1].w};
      float vi[8] = {vi4[2 * m].x, vi4[2 * m].y, vi4[2 * m].z, vi4[2 * m].w, vi4[2 * m + 1].x, vi4[2 * m + 1].y, vi4[2 * m + 1].z, vi4[2 * m + 1].w};
#pragma unroll
      for (int k = 0; k < 8; k++) { vr[k] = 2.f * (vr[k] + p.x); vi[k] = -2.f * (vi[k] + p.y); p = cmul(p, lam); }
      const uint4 pr = make_uint4(pack_bf16(vr[0], vr[1]), pack_bf16(vr[2], vr[3]), pack_bf16(vr[4], vr[5]), pack_bf16(vr[6], vr[7]));
      const uint4 pi = make_uint4(pack_bf16(vi[0], vi[1]), pack_bf16(vi[2], vi[3]), pack_bf16(vi[4], vi[5]), pack_bf16(vi[6], vi[7]));
      const int m8 = qi * 4 + m;
      *reinterpret_cast<uint4*>(smem + ch * 128 + ((m8 ^ (ch & 7)) << 4)) = pr;
      *reinterpret_cast<uint4*>(smem + (DM + ch) * 128 + ((m8 ^ (ch & 7)) << 4)) = pi;
    }
  }
  fence_async_smem();
  named_bar(1, 256);
  const int wg = warp >> 2, w = warp & 3;
  float acc[112];
#pragma unroll 1
  for (int kc = 0; kc < 14; kc++) {
    const int i = kc * 2 + wg, st = i % 3;
    mbar_wait(bar + i * 8, 0);
    const uint32_t bb = sb + S2_A + st * XT_BYTES;
    wg_fence();
#pragma unroll
    for (int kk = 0; kk < 4; kk++) {
      const uint64_t da = desc_sw128(sb + (kc * 64 + kk * 16) * 128);
      wgmma_ss_n112_ta(acc, da, desc_sw128(bb + kk * 32), (kc | kk) != 0);
      wgmma_ss_n112_ta(acc + 56, da, desc_sw128(bb + 14336 + kk * 32), (kc | kk) != 0);
    }
    wg_commit();
    wg_wait<0>();
    if (lane == 0) mbar_arrive(bar + (28 + st) * 8);
  }
  const int g = lane >> 2, q = lane & 3;
  named_bar(1, 256);
  float* stg = reinterpret_cast<float*>(smem);
#pragma unroll
  for (int r = 0; r < 2; r++)
#pragma unroll
    for (int nt = 0; nt < 28; nt++)
      *reinterpret_cast<float2*>(stg + (w * 16 + g + r * 8) * 456 + wg * 224 + nt * 8 + 2 * q) = make_float2(acc[nt * 4 + r * 2], acc[nt * 4 + r * 2 + 1]);
  named_bar(1, 256);
  for (int it = tid; it < 64 * 112; it += 256) {
    const int tl = it / 112, d = (it % 112) * 4;
    const float4 y = *reinterpret_cast<const float4*>(stg + tl * 456 + d);
    const uint2 xu = *reinterpret_cast<const uint2*>(args.x + (size_t)(t0 + tl) * DM + d), du = *reinterpret_cast<const uint2*>(args.dskip + d);
    const float gv = sg[tl];
    float4 o;
    o.x = gv * (y.x + rbf(__uint_as_float(xu.x << 16) * __uint_as_float(du.x << 16)));
    o.y = gv * (y.y + rbf(__uint_as_float(xu.x & 0xFFFF0000u) * __uint_as_float(du.x & 0xFFFF0000u)));
    o.z = gv * (y.z + rbf(__uint_as_float(xu.y << 16) * __uint_as_float(du.y << 16)));
    o.w = gv * (y.w + rbf(__uint_as_float(xu.y & 0xFFFF0000u) * __uint_as_float(du.y & 0xFFFF0000u)));
    red_v4(args.out + (size_t)(t0 + tl) * DM + d, o.x, o.y, o.z, o.w);
  }
  KT_END(2);
}
struct AttnArgs {
  uint32_t* flag;
  uint32_t* ticket;
  const float* omg;
  float* out;
  uint32_t total_ctas;
};
#define AT_SPLIT_V 56
constexpr int AT_SPLIT = AT_SPLIT_V;
constexpr int AT_ITEMS = AT_SPLIT * 2 + (NSEG - AT_SPLIT) * 8;
constexpr int AT_X = 2 * 7 * 4096;
constexpr int AT_T = 7 * 5120;
constexpr int AT_OFF_K = AT_X, AT_OFF_Y = AT_X + 2 * AT_T;
constexpr int AT_OFF_P = AT_X + 4 * AT_T;
constexpr int AT_OFF_BAR = AT_OFF_P + 2 * 2 * 3072;
constexpr int AT_STG = 32 * 68 * 4;
constexpr int AT_OFF_STG = AT_OFF_BAR + 256;
constexpr int AT_SMEM = AT_OFF_STG + 2 * AT_STG;
constexpr uint32_t FLAG_TARGET = 112;

__device__ __forceinline__ void attn_decode(int item, int& s, int& p0, int& np) {
  if (item < AT_SPLIT * 2) { s = item >> 1; p0 = (item & 1) * 4; np = 4; }
  else { const int i = item - AT_SPLIT * 2; s = AT_SPLIT + (i >> 3); p0 = i & 7; np = 1; }
}

#define ATS(i) do {} while (0)
__device__ __forceinline__ void attn_consumer(uint8_t* smem, uint32_t sb, const AttnArgs& args, int wg, int w, int lane) {
  const uint32_t bar = sb + AT_OFF_BAR;
  volatile int* s_item = reinterpret_cast<volatile int*>(smem + AT_OFF_BAR + 128);
  float* stg = reinterpret_cast<float*>(smem + AT_OFF_STG + wg * AT_STG);
  const int g = lane >> 2, q = lane & 3;
  const int C0 = wg * 4;
  int m = 0;
  long long tprev = clock64(); (void)tprev;
  for (int n = 0;; n++) {
    mbar_wait(bar + (0 + (n & 1)) * 8, (n >> 1) & 1);
    ATS(0);
    const int item = s_item[n & 1];
    if (item >= AT_ITEMS) break;
    int s, p0, np;
    attn_decode(item, s, p0, np);
    const uint64_t dx = desc_sw128(sb + (n & 1) * (7 * 4096));
    float acc[4][16];
    float om4[4];
#pragma unroll
    for (int i = 0; i < 4; i++) om4[i] = args.omg[s * SEG + i * 8 + ((w * 32 + lane) >> 4)];
#pragma unroll 1
    for (int pp = 0; pp < np; pp++, m++) {
      const uint64_t dk = desc_sw128(sb + AT_OFF_K + wg * AT_T);
      mbar_wait(bar + 4 * 8, m & 1);
      ATS(1);
      float sc[20];
      wg_fence();
#pragma unroll
      for (int kc = 0; kc < 7; kc++)
#pragma unroll
        for (int kk = 0; kk < 4; kk++) wgmma_ss_n40(sc, dx + (uint64_t)(kc * 256 + kk * 2), dk + (uint64_t)(kc * 320 + kk * 2), (kc | kk) != 0);
      wg_commit();
      wg_wait<0>();
      __syncwarp();
      if (lane == 0) { mbar_arrive(bar + 5 * 8); if (pp == np - 1) mbar_arrive(bar + (2 + (n & 1)) * 8); }
      ATS(2);
      const uint32_t pbuf = sb + AT_OFF_P + (m & 1) * (2 * 3072);
      if (w < 2) {
#pragma unroll
        for (int r = 0; r < 2; r++) {
          const int t = w * 16 + g + r * 8;
          float v[10];
          float mx = -3.0e38f;
#pragma unroll
          for (int nt = 0; nt < 5; nt++)
#pragma unroll
            for (int e = 0; e < 2; e++) {
              const int key = nt * 8 + 2 * q + e;
              const float x = (key - NMEM <= t) ? sc[nt * 4 + r * 2 + e] : -1.0e9f;
              v[nt * 2 + e] = x; mx = fmaxf(mx, x);
            }
          mx = fmaxf(mx, __shfl_xor_sync(~0u, mx, 1));
          mx = fmaxf(mx, __shfl_xor_sync(~0u, mx, 2));
          float l = 0.f;
#pragma unroll
          for (int k = 0; k < 10; k++) { v[k] = ex2((v[k] - mx) * L2E); l += v[k]; }
          l += __shfl_xor_sync(~0u, l, 1);
          l += __shfl_xor_sync(~0u, l, 2);
          const float rl = __fdividef(1.f, l);
          const uint32_t dst = pbuf + wg * 3072 + (2 * w + r) * 768 + g * 16 + q * 4;
#pragma unroll
          for (int nt = 0; nt < 5; nt++) asm volatile("st.shared.u32 [%0], %1;" ::"r"(dst + nt * 128), "r"(pack_bf16(v[2 * nt] * rl, v[2 * nt + 1] * rl)) : "memory");
        }
        fence_async_smem();
      }
      ATS(3);
      named_bar(1, 256);
      ATS(4);
      const uint64_t dp = ((uint64_t)((pbuf & 0x3FFFF) >> 4)) | ((uint64_t)(128 >> 4) << 16) | ((uint64_t)(768 >> 4) << 32);
      const uint64_t dy = desc_sw128(sb + AT_OFF_Y);
      mbar_wait(bar + 6 * 8, m & 1);
      ATS(5);
      wg_fence();
#pragma unroll
      for (int c = 0; c < 4; c++) {
        const int cc = min(C0 + c, 6);
#pragma unroll
        for (int hk = 0; hk < 6; hk++) {
          const int hd = hk / 3, kk = hk % 3;
          wgmma_ss_n32_ta(acc[c], dy + (uint64_t)(hd * (AT_T >> 4) + cc * 320 + kk * 128), dp + (uint64_t)(hd * 192 + kk * 16), (pp | hk) != 0);
        }
      }
      wg_commit();
      wg_wait<0>();
      __syncwarp();
      if (lane == 0) mbar_arrive(bar + 7 * 8);
      ATS(6);
    }
    {
      const int tid7 = w * 32 + lane;
#pragma unroll
      for (int c = 0; c < 4; c++) {
        if (C0 + c < 7) {
#pragma unroll
          for (int nt = 0; nt < 4; nt++) {
            stg[(8 * nt + 2 * q) * 68 + 16 * w + g] = acc[c][4 * nt];
            stg[(8 * nt + 2 * q + 1) * 68 + 16 * w + g] = acc[c][4 * nt + 1];
            stg[(8 * nt + 2 * q) * 68 + 16 * w + g + 8] = acc[c][4 * nt + 2];
            stg[(8 * nt + 2 * q + 1) * 68 + 16 * w + g + 8] = acc[c][4 * nt + 3];
          }
          named_bar(2 + wg, 128);
#pragma unroll
          for (int i = 0; i < 4; i++) {
            const int row = i * 8 + (tid7 >> 4), col = (tid7 & 15) * 4;
            const float4 v = *reinterpret_cast<const float4*>(stg + row * 68 + col);
            const float om = om4[i];
            red_v4(args.out + (size_t)(s * SEG + row) * DM + (C0 + c) * 64 + col, om * v.x, om * v.y, om * v.z, om * v.w);
          }
          named_bar(2 + wg, 128);
        }
      }
    }
    ATS(7);
  }
}

__global__ void __launch_bounds__(384, 1)
attn_kernel(const __grid_constant__ CUtensorMap tm_x, const __grid_constant__ CUtensorMap tm_k, const __grid_constant__ CUtensorMap tm_y, AttnArgs args) {
  extern __shared__ __align__(1024) uint8_t smem[];
  const uint32_t sb = smem_u32(smem), bar = sb + AT_OFF_BAR;
  volatile int* s_item = reinterpret_cast<volatile int*>(smem + AT_OFF_BAR + 128);
  const int tid = threadIdx.x, warp = tid >> 5, lane = tid & 31;
  KT_START(3);
  if (tid == 0) {
    mbar_init(bar + 0 * 8, 1); mbar_init(bar + 1 * 8, 1); mbar_init(bar + 2 * 8, 8); mbar_init(bar + 3 * 8, 8);
    mbar_init(bar + 4 * 8, 1); mbar_init(bar + 5 * 8, 8); mbar_init(bar + 6 * 8, 1); mbar_init(bar + 7 * 8, 8);
    asm volatile("fence.mbarrier_init.release.cluster;" ::: "memory");
  }
  for (int i = tid; i < AT_OFF_BAR / 16; i += 384) *reinterpret_cast<uint4*>(smem + i * 16) = make_uint4(0, 0, 0, 0);
  fence_async_smem();
  __syncthreads();
  const int wg = __shfl_sync(0xffffffffu, warp >> 2, 0);
  if (wg == 2) {
    asm volatile("setmaxnreg.dec.sync.aligned.u32 40;");
    if (tid == 256) {
      int m = 0;
      for (int n = 0;; n++) {
        const int sl = n & 1;
        if (n >= 2) mbar_wait(bar + (2 + sl) * 8, ((n >> 1) - 1) & 1);
        const int item = (int)atomicAdd(args.ticket, 1u);
        s_item[sl] = item;
        if (item >= AT_ITEMS) {
          mbar_arrive(bar + sl * 8);
          if (atomicAdd(args.ticket + 1, 1u) == args.total_ctas - 1) {
            for (int i = 0; i < NSEG; i++) args.flag[i] = 0u;
            args.ticket[0] = 0u; args.ticket[1] = 0u;
          }
          break;
        }
        int s, p0, np;
        attn_decode(item, s, p0, np);
        mbar_expect_tx(bar + sl * 8, 7 * 4096);
        tma_load_3d(sb + sl * (7 * 4096), &tm_x, 0, s * SEG, 0, bar + sl * 8);
        { int it = 0; while (ld_acquire(args.flag + s) < FLAG_TARGET && ++it < SPIN_LIMIT) __nanosleep(100); }
        fence_async_all();
        for (int pp = 0; pp < np; pp++, m++) {
          const int row = (((p0 + pp) * 2) * NSEG + s) * LKEY;
          if (m >= 1) mbar_wait(bar + 5 * 8, (m - 1) & 1);
          mbar_expect_tx(bar + 4 * 8, 2 * AT_T);
          tma_load_3d(sb + AT_OFF_K, &tm_k, 0, row, 0, bar + 4 * 8);
          tma_load_3d(sb + AT_OFF_K + AT_T, &tm_k, 0, row + NSEG * LKEY, 0, bar + 4 * 8);
          if (m >= 1) mbar_wait(bar + 7 * 8, (m - 1) & 1);
          mbar_expect_tx(bar + 6 * 8, 2 * AT_T);
          tma_load_3d(sb + AT_OFF_Y, &tm_y, 0, row, 0, bar + 6 * 8);
          tma_load_3d(sb + AT_OFF_Y + AT_T, &tm_y, 0, row + NSEG * LKEY, 0, bar + 6 * 8);
        }
      }
    }
  } else {
    asm volatile("setmaxnreg.inc.sync.aligned.u32 232;");
    attn_consumer(smem, sb, args, wg, warp & 3, lane);
    KT_END(3);
  }
}
__device__ bf16 g_Kall[(size_t)NH * NSEG * LKEY * DM];
__device__ bf16 g_Yall[(size_t)NH * NSEG * LKEY * DM];
__device__ uint32_t g_M[65 * 1792];
__device__ float4 g_S[(size_t)NSEG * NH * 5 * 32 + (size_t)NSEG * NJ * 16 * 16 * 8];
__device__ uint32_t g_flag[NSEG + 64];
__device__ float g_hloc[2 * DM * SEQ];
__device__ float2 g_hend[16 * DM];
__device__ float g_omg[2 * SEQ];
__device__ float4 g_tab[2 * DM];
__device__ uint32_t g_dbg[112 * 1024 + 112 * 4 + 112 * 8];

typedef CUresult (*EncodeFn)(CUtensorMap*, CUtensorMapDataType, cuuint32_t, void*, const cuuint64_t*, const cuuint64_t*, const cuuint32_t*,
                             const cuuint32_t*, CUtensorMapInterleave, CUtensorMapSwizzle, CUtensorMapL2promotion, CUtensorMapFloatOOBfill);

static bool make_map_2d(EncodeFn enc, CUtensorMap* m, const void* ptr, uint64_t cols, uint64_t rows, uint32_t box_cols, uint32_t box_rows) {
  cuuint64_t dims[2] = {cols, rows};
  cuuint64_t strides[1] = {cols * 2};
  cuuint32_t box[2] = {box_cols, box_rows};
  cuuint32_t es[2] = {1, 1};
  return enc(m, CU_TENSOR_MAP_DATA_TYPE_BFLOAT16, 2, const_cast<void*>(ptr), dims, strides, box, es, CU_TENSOR_MAP_INTERLEAVE_NONE,
             CU_TENSOR_MAP_SWIZZLE_128B, CU_TENSOR_MAP_L2_PROMOTION_L2_256B, CU_TENSOR_MAP_FLOAT_OOB_FILL_NONE) == CUDA_SUCCESS;
}
static bool make_map_rows(EncodeFn enc, CUtensorMap* m, const void* ptr, uint64_t rows, uint32_t box_rows) {
  cuuint64_t dims[3] = {64, rows, 7};
  cuuint64_t strides[2] = {(cuuint64_t)DM * 2, 128};
  cuuint32_t box[3] = {64, box_rows, 7};
  cuuint32_t es[3] = {1, 1, 1};
  return enc(m, CU_TENSOR_MAP_DATA_TYPE_BFLOAT16, 3, const_cast<void*>(ptr), dims, strides, box, es, CU_TENSOR_MAP_INTERLEAVE_NONE,
             CU_TENSOR_MAP_SWIZZLE_128B, CU_TENSOR_MAP_L2_PROMOTION_L2_256B, CU_TENSOR_MAP_FLOAT_OOB_FILL_NONE) == CUDA_SUCCESS;
}
static bool make_map_xperm(EncodeFn enc, CUtensorMap* m, const void* ptr) {
  cuuint64_t dims[4] = {(cuuint64_t)DM, 2, 64, 16};
  cuuint64_t strides[3] = {(cuuint64_t)DM * 2, (cuuint64_t)DM * 2 * 32, (cuuint64_t)DM * 2 * 2};
  cuuint32_t box[4] = {64, 2, 4, 16};
  cuuint32_t es[4] = {1, 1, 1, 1};
  return enc(m, CU_TENSOR_MAP_DATA_TYPE_BFLOAT16, 4, const_cast<void*>(ptr), dims, strides, box, es, CU_TENSOR_MAP_INTERLEAVE_NONE,
             CU_TENSOR_MAP_SWIZZLE_128B, CU_TENSOR_MAP_L2_PROMOTION_L2_256B, CU_TENSOR_MAP_FLOAT_OOB_FILL_NONE) == CUDA_SUCCESS;
}

#define N_ATTN 8
struct HostState {
  bool init, ok, use_cluster;
  CUtensorMap tx, tq, tk, tv, to, tka, tya, tbre, tbim, txp, tcre, tcim, tx3, tk3, ty3;
  void *pK, *pY, *pM, *pS, *pF, *pD, *pH, *pE, *pO, *pT;
  cudaStream_t side, side2;
  cudaEvent_t ev_start, ev_join, ev_gate, ev_join2;
  int n_free, n_attn;
  const void* key[17];
  void* key_out;
};
static HostState g_hs;

}

extern "C" void kernel_launch(void* const* d_in, const int* in_sizes, int n_in, void* d_out, int out_size) {
  HostState& S = g_hs;
  (void)in_sizes; (void)n_in; (void)out_size;
  cudaStream_t st = cudaStreamPerThread;
  bool same = S.init;
  for (int i = 0; i < 17 && same; i++) same = S.key[i] == d_in[i];
  if (!same) {
    EncodeFn enc = nullptr;
    cudaDriverEntryPointQueryResult qr;
    cudaGetDriverEntryPoint("cuTensorMapEncodeTiled", (void**)&enc, cudaEnableDefault, &qr);
    cudaGetSymbolAddress(&S.pK, g_Kall); cudaGetSymbolAddress(&S.pY, g_Yall); cudaGetSymbolAddress(&S.pM, g_M); cudaGetSymbolAddress(&S.pS, g_S);
    cudaGetSymbolAddress(&S.pF, g_flag); cudaGetSymbolAddress(&S.pD, g_dbg); cudaGetSymbolAddress(&S.pH, g_hloc); cudaGetSymbolAddress(&S.pE, g_hend);
    cudaGetSymbolAddress(&S.pO, g_omg); cudaGetSymbolAddress(&S.pT, g_tab);
    S.ok = enc && make_map_2d(enc, &S.tx, d_in[0], DM, SEQ, 64, 32) && make_map_2d(enc, &S.tq, d_in[11], 4096, DM, 64, 64) &&
           make_map_2d(enc, &S.tk, d_in[12], 4096, DM, 64, 224) && make_map_2d(enc, &S.tv, d_in[13], 4096, DM, 64, 224) &&
           make_map_2d(enc, &S.to, d_in[14], DM, 4096, 64, 256) && make_map_2d(enc, &S.tka, S.pK, DM, NH * NSEG * LKEY, 64, LKEY) &&
           make_map_2d(enc, &S.tya, S.pY, DM, NH * NSEG * LKEY, 64, LKEY) && make_map_2d(enc, &S.tbre, d_in[3], DM, DM, 64, 64) &&
           make_map_2d(enc, &S.tbim, d_in[4], DM, DM, 64, 64) && make_map_xperm(enc, &S.txp, d_in[0]) &&
           make_map_2d(enc, &S.tcre, d_in[5], DM, DM, 64, 224) && make_map_2d(enc, &S.tcim, d_in[6], DM, DM, 64, 224) &&
           make_map_rows(enc, &S.tx3, d_in[0], SEQ, SEG) && make_map_rows(enc, &S.tk3, S.pK, NH * NSEG * LKEY, LKEY) && make_map_rows(enc, &S.ty3, S.pY, NH * NSEG * LKEY, LKEY);
    if (!S.init) {
      cudaFuncSetAttribute(chain_kernel<true>, cudaFuncAttributeMaxDynamicSharedMemorySize, SMEM_CHAIN);
      cudaFuncSetAttribute(chain_kernel<true>, cudaFuncAttributeNonPortableClusterSizeAllowed, 1);
      cudaFuncSetAttribute(chain_kernel<false>, cudaFuncAttributeMaxDynamicSharedMemorySize, SMEM_CHAIN);
      cudaFuncSetAttribute(ssm1_kernel, cudaFuncAttributeMaxDynamicSharedMemorySize, S1_SMEM);
      cudaFuncSetAttribute(ssm2_kernel, cudaFuncAttributeMaxDynamicSharedMemorySize, S2_SMEM);
      cudaFuncSetAttribute(attn_kernel, cudaFuncAttributeMaxDynamicSharedMemorySize, AT_SMEM);
      cudaLaunchConfig_t cfg = {};
      cfg.gridDim = dim3(112); cfg.blockDim = dim3(CHAIN_THREADS); cfg.dynamicSmemBytes = SMEM_CHAIN;
      cudaLaunchAttribute at[1];
      at[0].id = cudaLaunchAttributeClusterDimension; at[0].val.clusterDim.x = 16; at[0].val.clusterDim.y = 1; at[0].val.clusterDim.z = 1;
      cfg.attrs = at; cfg.numAttrs = 1;
      int nc = 0;
      if (cudaOccupancyMaxActiveClusters(&nc, chain_kernel<true>, &cfg) != cudaSuccess) { nc = 0; (void)cudaGetLastError(); }
      S.use_cluster = nc >= 7;
      int sms = 132;
      cudaDeviceGetAttribute(&sms, cudaDevAttrMultiProcessorCount, 0);
      S.n_free = sms - 112 > 1 ? sms - 112 : 1;
      S.n_attn = S.n_free >= 16 ? N_ATTN : (S.n_free + 1) / 2;
      cudaStreamCreateWithFlags(&S.side, cudaStreamNonBlocking);
      cudaEventCreateWithFlags(&S.ev_start, cudaEventDisableTiming);
      cudaEventCreateWithFlags(&S.ev_join, cudaEventDisableTiming);
      cudaStreamCreateWithFlags(&S.side2, cudaStreamNonBlocking);
      cudaEventCreateWithFlags(&S.ev_gate, cudaEventDisableTiming);
      cudaEventCreateWithFlags(&S.ev_join2, cudaEventDisableTiming);
    }
    for (int i = 0; i < 17; i++) S.key[i] = d_in[i];
    S.init = true;
  }
  if (!S.ok) return;

  ChainArgs ca;
  ca.mem0 = (const bf16*)d_in[10]; ca.Mg = (uint32_t*)S.pM; ca.Sg = (float4*)S.pS; ca.flag = (uint32_t*)S.pF; ca.dbg = (uint32_t*)S.pD;
  {
    cudaLaunchConfig_t cfg = {};
    cfg.gridDim = dim3(112); cfg.blockDim = dim3(CHAIN_THREADS); cfg.dynamicSmemBytes = SMEM_CHAIN; cfg.stream = st;
    cudaLaunchAttribute at[2];
    at[0].id = cudaLaunchAttributeLaunchCompletionEvent; at[0].val.launchCompletionEvent.event = S.ev_start; at[0].val.launchCompletionEvent.flags = 0;
    at[1].id = cudaLaunchAttributeClusterDimension; at[1].val.clusterDim.x = 16; at[1].val.clusterDim.y = 1; at[1].val.clusterDim.z = 1;
    cfg.attrs = at; cfg.numAttrs = S.use_cluster ? 2 : 1;
    if (S.use_cluster) cudaLaunchKernelEx(&cfg, chain_kernel<true>, S.tx, S.tq, S.tk, S.tv, S.to, S.tka, S.tya, S.tx3, ca);
    else cudaLaunchKernelEx(&cfg, chain_kernel<false>, S.tx, S.tq, S.tk, S.tv, S.to, S.tka, S.tya, S.tx3, ca);
  }
  SsmArgs sa;
  sa.lam_re = (const bf16*)d_in[1]; sa.lam_im = (const bf16*)d_in[2]; sa.log_dt = (const bf16*)d_in[7]; sa.dskip = (const bf16*)d_in[8];
  sa.x = (const bf16*)d_in[0]; sa.gate_w = (const bf16*)d_in[16];
  sa.hloc = (float*)S.pH; sa.hend = (float2*)S.pE; sa.omg = (float*)S.pO; sa.gate = (float*)S.pO + SEQ; sa.tab = (float4*)S.pT; sa.out = (float*)d_out;
  AttnArgs aa;
  aa.flag = (uint32_t*)S.pF; aa.ticket = (uint32_t*)S.pF + NSEG; aa.omg = (const float*)S.pO; aa.out = (float*)d_out;
  const int n_attn2 = S.n_free - S.n_attn > 0 ? S.n_free - S.n_attn : 0;
  aa.total_ctas = (uint32_t)(S.n_attn + n_attn2);
  cudaStreamWaitEvent(S.side, S.ev_start, 0);
  cudaMemsetAsync(d_out, 0, sizeof(float) * SEQ * DM, S.side);
  gate_kernel<<<64, 128, 0, S.side>>>(sa);
  cudaEventRecord(S.ev_gate, S.side);
  attn_kernel<<<S.n_attn, 384, AT_SMEM, S.side>>>(S.tx3, S.tk3, S.ty3, aa);
  cudaStreamWaitEvent(S.side2, S.ev_gate, 0);
  ssm1_kernel<<<dim3(7, 16), 160, S1_SMEM, S.side2>>>(S.tbre, S.tbim, S.txp, sa);
  ssm2_kernel<<<32, 288, S2_SMEM, S.side2>>>(S.tcre, S.tcim, sa);
  if (n_attn2 > 0) attn_kernel<<<n_attn2, 384, AT_SMEM, S.side2>>>(S.tx3, S.tk3, S.ty3, aa);
  cudaEventRecord(S.ev_join, S.side);
  cudaEventRecord(S.ev_join2, S.side2);
  cudaStreamWaitEvent(st, S.ev_join, 0);
  cudaStreamWaitEvent(st, S.ev_join2, 0);
}
```

```cpp
#include <cuda_runtime.h>
#include <cuda_bf16.h>
#include <cuda.h>
#include <stdint.h>

typedef __nv_bfloat16 bf16;

namespace {

constexpr int NH = 16, DM = 448, DH = 256, SEQ = 2048, SEG = 32, NSEG = 64, NJ = 7, NMEM = 8, LKEY = 40;
constexpr int SPIN_LIMIT = 1 << 22;

#define KT_START(k) do {} while (0)
#define KT_END(k) do {} while (0)

__device__ __forceinline__ uint32_t smem_u32(const void* p) { return (uint32_t)__cvta_generic_to_shared(p); }
__device__ __forceinline__ void mbar_init(uint32_t a, uint32_t c) { asm volatile("mbarrier.init.shared.b64 [%0], %1;" ::"r"(a), "r"(c)); }
__device__ __forceinline__ void mbar_arrive(uint32_t a) { asm volatile("mbarrier.arrive.shared.b64 _, [%0];" ::"r"(a) : "memory"); }
__device__ __forceinline__ void mbar_expect_tx(uint32_t a, uint32_t b) { asm volatile("mbarrier.arrive.expect_tx.shared.b64 _, [%0], %1;" ::"r"(a), "r"(b) : "memory"); }
__device__ __forceinline__ bool mbar_try(uint32_t a, uint32_t parity) {
  uint32_t r;
  asm volatile("{\n.reg .pred p;\nmbarrier.try_wait.parity.shared.b64 p, [%1], %2;\nselp.u32 %0, 1, 0, p;\n}\n" : "=r"(r) : "r"(a), "r"(parity) : "memory");
  return r;
}
__device__ __forceinline__ bool mbar_try_cluster(uint32_t a, uint32_t parity) {
  uint32_t r;
  asm volatile("{\n.reg .pred p;\nmbarrier.try_wait.parity.acquire.cluster.shared.b64 p, [%1], %2;\nselp.u32 %0, 1, 0, p;\n}\n" : "=r"(r) : "r"(a), "r"(parity) : "memory");
  return r;
}
__device__ __forceinline__ bool mbar_test(uint32_t a, uint32_t parity) {
  uint32_t r;
  asm volatile("{\n.reg .pred p;\nmbarrier.test_wait.parity.shared.b64 p, [%1], %2;\nselp.u32 %0, 1, 0, p;\n}\n" : "=r"(r) : "r"(a), "r"(parity) : "memory");
  return r;
}
__device__ __forceinline__ void mbar_wait(uint32_t a, uint32_t parity) {
  int it = 0;
  while (!mbar_try(a, parity)) { if (++it > SPIN_LIMIT) break; }
}
__device__ __forceinline__ void mbar_wait_cluster(uint32_t a, uint32_t parity) {
  int it = 0;
  while (!mbar_try_cluster(a, parity)) { if (++it > SPIN_LIMIT) break; }
}
__device__ __forceinline__ uint32_t mapa(uint32_t a, uint32_t r) { uint32_t d; asm volatile("mapa.shared::cluster.u32 %0, %1, %2;" : "=r"(d) : "r"(a), "r"(r)); return d; }
__device__ __forceinline__ void cluster_sync_all() { asm volatile("barrier.cluster.arrive.aligned;\nbarrier.cluster.wait.aligned;" ::: "memory"); }
__device__ __forceinline__ void named_bar(int id, int n) { asm volatile("bar.sync %0, %1;" ::"r"(id), "r"(n) : "memory"); }
__device__ __forceinline__ void fence_async_smem() { asm volatile("fence.proxy.async.shared::cta;" ::: "memory"); }
__device__ __forceinline__ void fence_async_all() { asm volatile("fence.proxy.async;" ::: "memory"); }

__device__ __forceinline__ uint4 ld_vol_v4(const void* p) {
  uint4 v;
  asm volatile("ld.volatile.global.v4.u32 {%0,%1,%2,%3}, [%4];" : "=r"(v.x), "=r"(v.y), "=r"(v.z), "=r"(v.w) : "l"(p) : "memory");
  return v;
}
__device__ __forceinline__ uint32_t ld_acquire(const void* p) { uint32_t v; asm volatile("ld.acquire.gpu.global.u32 %0, [%1];" : "=r"(v) : "l"(p) : "memory"); return v; }
__device__ __forceinline__ void st_relaxed(void* p, uint32_t v) { asm volatile("st.relaxed.gpu.global.u32 [%0], %1;" ::"l"(p), "r"(v) : "memory"); }
__device__ __forceinline__ void red_v4(void* p, float a, float b, float c, float d) {
  asm volatile("red.relaxed.gpu.global.add.v4.f32 [%0], {%1,%2,%3,%4};" ::"l"(p), "f"(a), "f"(b), "f"(c), "f"(d) : "memory");
}
__device__ __forceinline__ void red_v2(void* p, float a, float b) {
  asm volatile("red.relaxed.gpu.global.add.v2.f32 [%0], {%1,%2};" ::"l"(p), "f"(a), "f"(b) : "memory");
}
__device__ __forceinline__ void red_u32(void* p, uint32_t v) { asm volatile("red.relaxed.gpu.global.add.u32 [%0], %1;" ::"l"(p), "r"(v) : "memory"); }
__device__ __forceinline__ void st_async_v4(uint32_t addr, float a, float b, float c, float d, uint32_t mbar) {
  asm volatile("st.async.shared::cluster.mbarrier::complete_tx::bytes.v4.f32 [%0], {%1,%2,%3,%4}, [%5];" ::"r"(addr), "f"(a), "f"(b), "f"(c), "f"(d), "r"(mbar) : "memory");
}

__device__ __forceinline__ void tma_load_2d(uint32_t dst, const CUtensorMap* tm, int c0, int c1, uint32_t mbar) {
  asm volatile("cp.async.bulk.tensor.2d.shared::cluster.global.mbarrier::complete_tx::bytes [%0], [%1, {%3, %4}], [%2];" ::"r"(dst), "l"(tm), "r"(mbar), "r"(c0), "r"(c1) : "memory");
}
__device__ __forceinline__ void tma_load_2d_mc(uint32_t dst, const CUtensorMap* tm, int c0, int c1, uint32_t mbar, uint16_t mask) {
  asm volatile("cp.async.bulk.tensor.2d.shared::cluster.global.mbarrier::complete_tx::bytes.multicast::cluster [%0], [%1, {%3, %4}], [%2], %5;" ::"r"(dst), "l"(tm), "r"(mbar), "r"(c0), "r"(c1), "h"(mask) : "memory");
}
__device__ __forceinline__ void tma_load_3d(uint32_t dst, const CUtensorMap* tm, int c0, int c1, int c2, uint32_t mbar) {
  asm volatile("cp.async.bulk.tensor.3d.shared::cluster.global.mbarrier::complete_tx::bytes [%0], [%1, {%3, %4, %5}], [%2];" ::"r"(dst), "l"(tm), "r"(mbar), "r"(c0), "r"(c1), "r"(c2) : "memory");
}
__device__ __forceinline__ void tma_load_4d(uint32_t dst, const CUtensorMap* tm, int c0, int c1, int c2, int c3, uint32_t mbar) {
  asm volatile("cp.async.bulk.tensor.4d.shared::cluster.global.mbarrier::complete_tx::bytes [%0], [%1, {%3, %4, %5, %6}], [%2];" ::"r"(dst), "l"(tm), "r"(mbar), "r"(c0), "r"(c1), "r"(c2), "r"(c3) : "memory");
}
__device__ __forceinline__ void tma_store_2d(const CUtensorMap* tm, int c0, int c1, uint32_t src) {
  asm volatile("cp.async.bulk.tensor.2d.global.shared::cta.bulk_group [%0, {%2, %3}], [%1];" ::"l"(tm), "r"(src), "r"(c0), "r"(c1) : "memory");
}
__device__ __forceinline__ void bulk_load(uint32_t dst, const void* src, uint32_t bytes, uint32_t mbar) {
  asm volatile("cp.async.bulk.shared::cluster.global.mbarrier::complete_tx::bytes [%0], [%1], %2, [%3];" ::"r"(dst), "l"(src), "r"(bytes), "r"(mbar) : "memory");
}
__device__ __forceinline__ void bulk_commit() { asm volatile("cp.async.bulk.commit_group;" ::: "memory"); }
template <int N> __device__ __forceinline__ void bulk_wait_read() { asm volatile("cp.async.bulk.wait_group.read %0;" ::"n"(N) : "memory"); }
template <int N> __device__ __forceinline__ void bulk_wait() { asm volatile("cp.async.bulk.wait_group %0;" ::"n"(N) : "memory"); }

__device__ __forceinline__ void wg_fence() { asm volatile("wgmma.fence.sync.aligned;" ::: "memory"); }
__device__ __forceinline__ void wg_commit() { asm volatile("wgmma.commit_group.sync.aligned;" ::: "memory"); }
template <int N> __device__ __forceinline__ void wg_wait() { asm volatile("wgmma.wait_group.sync.aligned %0;" ::"n"(N) : "memory"); }

__device__ __forceinline__ uint64_t desc_sw128(uint32_t addr) {
  return ((uint64_t)((addr & 0x3FFFF) >> 4)) | ((uint64_t)1 << 16) | ((uint64_t)(1024 >> 4) << 32) | ((uint64_t)1 << 62);
}

__device__ __forceinline__ uint32_t pack_bf16(float lo, float hi) {
  uint32_t r;
  asm("cvt.rn.bf16x2.f32 %0, %1, %2;" : "=r"(r) : "f"(hi), "f"(lo));
  return r;
}
__device__ __forceinline__ void mma16816(float* d, uint32_t a0, uint32_t a1, uint32_t a2, uint32_t a3, uint32_t b0, uint32_t b1) {
  asm volatile("mma.sync.aligned.m16n8k16.row.col.f32.bf16.bf16.f32 {%0,%1,%2,%3}, {%4,%5,%6,%7}, {%8,%9}, {%0,%1,%2,%3};"
               : "+f"(d[0]), "+f"(d[1]), "+f"(d[2]), "+f"(d[3]) : "r"(a0), "r"(a1), "r"(a2), "r"(a3), "r"(b0), "r"(b1));
}
__device__ __forceinline__ void mma1688(float* d, uint32_t a0, uint32_t a1, uint32_t b0) {
  asm volatile("mma.sync.aligned.m16n8k8.row.col.f32.bf16.bf16.f32 {%0,%1,%2,%3}, {%4,%5}, {%6}, {%0,%1,%2,%3};"
               : "+f"(d[0]), "+f"(d[1]), "+f"(d[2]), "+f"(d[3]) : "r"(a0), "r"(a1), "r"(b0));
}
__device__ __forceinline__ void ldsm_x4(uint32_t* r, uint32_t addr) {
  asm volatile("ldmatrix.sync.aligned.m8n8.x4.shared.b16 {%0,%1,%2,%3}, [%4];" : "=r"(r[0]), "=r"(r[1]), "=r"(r[2]), "=r"(r[3]) : "r"(addr) : "memory");
}
__device__ __forceinline__ void ldsm_x4_t(uint32_t* r, uint32_t addr) {
  asm volatile("ldmatrix.sync.aligned.m8n8.x4.trans.shared.b16 {%0,%1,%2,%3}, [%4];" : "=r"(r[0]), "=r"(r[1]), "=r"(r[2]), "=r"(r[3]) : "r"(addr) : "memory");
}
__device__ __forceinline__ void ldsm_x2_t(uint32_t* r, uint32_t addr) {
  asm volatile("ldmatrix.sync.aligned.m8n8.x2.trans.shared.b16 {%0,%1}, [%2];" : "=r"(r[0]), "=r"(r[1]) : "r"(addr) : "memory");
}
__device__ __forceinline__ void stsm_x4_t(uint32_t addr, uint32_t r0, uint32_t r1, uint32_t r2, uint32_t r3) {
  asm volatile("stmatrix.sync.aligned.m8n8.x4.trans.shared.b16 [%0], {%1,%2,%3,%4};" ::"r"(addr), "r"(r0), "r"(r1), "r"(r2), "r"(r3) : "memory");
}
__device__ __forceinline__ uint32_t movm_t(uint32_t a) { uint32_t d; asm volatile("movmatrix.sync.aligned.m8n8.trans.b16 %0, %1;" : "=r"(d) : "r"(a)); return d; }
__device__ __forceinline__ float ex2(float x) { float y; asm("ex2.approx.ftz.f32 %0, %1;" : "=f"(y) : "f"(x)); return y; }

__device__ __forceinline__ void wgmma_ss_n112(float* d, uint64_t descA, uint64_t descB, int scaleD) {
  asm volatile("{\n.reg .pred p;\nsetp.ne.b32 p, %58, 0;\n"
    "wgmma.mma_async.sync.aligned.m64n112k16.f32.bf16.bf16 {%0,%1,%2,%3,%4,%5,%6,%7,%8,%9,%10,%11,%12,%13,%14,%15,%16,%17,%18,%19,%20,%21,%22,%23,%24,%25,%26,%27,%28,%29,%30,%31,%32,%33,%34,%35,%36,%37,%38,%39,%40,%41,%42,%43,%44,%45,%46,%47,%48,%49,%50,%51,%52,%53,%54,%55}, %56, %57, p, 1, 1, 0, 0;\n}\n"
    : "+f"(d[0]),"+f"(d[1]),"+f"(d[2]),"+f"(d[3]),"+f"(d[4]),"+f"(d[5]),"+f"(d[6]),"+f"(d[7]),"+f"(d[8]),"+f"(d[9]),"+f"(d[10]),"+f"(d[11]),"+f"(d[12]),"+f"(d[13]),"+f"(d[14]),"+f"(d[15]),"+f"(d[16]),"+f"(d[17]),"+f"(d[18]),"+f"(d[19]),"+f"(d[20]),"+f"(d[21]),"+f"(d[22]),"+f"(d[23]),"+f"(d[24]),"+f"(d[25]),"+f"(d[26]),"+f"(d[27]),"+f"(d[28]),"+f"(d[29]),"+f"(d[30]),"+f"(d[31]),"+f"(d[32]),"+f"(d[33]),"+f"(d[34]),"+f"(d[35]),"+f"(d[36]),"+f"(d[37]),"+f"(d[38]),"+f"(d[39]),"+f"(d[40]),"+f"(d[41]),"+f"(d[42]),"+f"(d[43]),"+f"(d[44]),"+f"(d[45]),"+f"(d[46]),"+f"(d[47]),"+f"(d[48]),"+f"(d[49]),"+f"(d[50]),"+f"(d[51]),"+f"(d[52]),"+f"(d[53]),"+f"(d[54]),"+f"(d[55])
    : "l"(descA), "l"(descB), "r"(scaleD));
}
__device__ __forceinline__ void wgmma_ss_n112_ta(float* d, uint64_t descA, uint64_t descB, int scaleD) {
  asm volatile("{\n.reg .pred p;\nsetp.ne.b32 p, %58, 0;\n"
    "wgmma.mma_async.sync.aligned.m64n112k16.f32.bf16.bf16 {%0,%1,%2,%3,%4,%5,%6,%7,%8,%9,%10,%11,%12,%13,%14,%15,%16,%17,%18,%19,%20,%21,%22,%23,%24,%25,%26,%27,%28,%29,%30,%31,%32,%33,%34,%35,%36,%37,%38,%39,%40,%41,%42,%43,%44,%45,%46,%47,%48,%49,%50,%51,%52,%53,%54,%55}, %56, %57, p, 1, 1, 1, 0;\n}\n"
    : "+f"(d[0]),"+f"(d[1]),"+f"(d[2]),"+f"(d[3]),"+f"(d[4]),"+f"(d[5]),"+f"(d[6]),"+f"(d[7]),"+f"(d[8]),"+f"(d[9]),"+f"(d[10]),"+f"(d[11]),"+f"(d[12]),"+f"(d[13]),"+f"(d[14]),"+f"(d[15]),"+f"(d[16]),"+f"(d[17]),"+f"(d[18]),"+f"(d[19]),"+f"(d[20]),"+f"(d[21]),"+f"(d[22]),"+f"(d[23]),"+f"(d[24]),"+f"(d[25]),"+f"(d[26]),"+f"(d[27]),"+f"(d[28]),"+f"(d[29]),"+f"(d[30]),"+f"(d[31]),"+f"(d[32]),"+f"(d[33]),"+f"(d[34]),"+f"(d[35]),"+f"(d[36]),"+f"(d[37]),"+f"(d[38]),"+f"(d[39]),"+f"(d[40]),"+f"(d[41]),"+f"(d[42]),"+f"(d[43]),"+f"(d[44]),"+f"(d[45]),"+f"(d[46]),"+f"(d[47]),"+f"(d[48]),"+f"(d[49]),"+f"(d[50]),"+f"(d[51]),"+f"(d[52]),"+f"(d[53]),"+f"(d[54]),"+f"(d[55])
    : "l"(descA), "l"(descB), "r"(scaleD));
}
__device__ __forceinline__ void wgmma_rs_n32(float* d, const uint32_t* a, uint64_t descB, int scaleD) {
  asm volatile("{\n.reg .pred p;\nsetp.ne.b32 p, %21, 0;\n"
    "wgmma.mma_async.sync.aligned.m64n32k16.f32.bf16.bf16 {%0,%1,%2,%3,%4,%5,%6,%7,%8,%9,%10,%11,%12,%13,%14,%15}, {%16,%17,%18,%19}, %20, p, 1, 1, 0;\n}\n"
    : "+f"(d[0]),"+f"(d[1]),"+f"(d[2]),"+f"(d[3]),"+f"(d[4]),"+f"(d[5]),"+f"(d[6]),"+f"(d[7]),"+f"(d[8]),"+f"(d[9]),"+f"(d[10]),"+f"(d[11]),"+f"(d[12]),"+f"(d[13]),"+f"(d[14]),"+f"(d[15])
    : "r"(a[0]), "r"(a[1]), "r"(a[2]), "r"(a[3]), "l"(descB), "r"(scaleD));
}
__device__ __forceinline__ void wgmma_ss_n128(float* d, uint64_t descA, uint64_t descB, int scaleD) {
  asm volatile("{\n.reg .pred p;\nsetp.ne.b32 p, %66, 0;\n"
    "wgmma.mma_async.sync.aligned.m64n128k16.f32.bf16.bf16 {%0,%1,%2,%3,%4,%5,%6,%7,%8,%9,%10,%11,%12,%13,%14,%15,%16,%17,%18,%19,%20,%21,%22,%23,%24,%25,%26,%27,%28,%29,%30,%31,%32,%33,%34,%35,%36,%37,%38,%39,%40,%41,%42,%43,%44,%45,%46,%47,%48,%49,%50,%51,%52,%53,%54,%55,%56,%57,%58,%59,%60,%61,%62,%63}, %64, %65, p, 1, 1, 0, 0;\n}\n"
    : "+f"(d[0]),"+f"(d[1]),"+f"(d[2]),"+f"(d[3]),"+f"(d[4]),"+f"(d[5]),"+f"(d[6]),"+f"(d[7]),"+f"(d[8]),"+f"(d[9]),"+f"(d[10]),"+f"(d[11]),"+f"(d[12]),"+f"(d[13]),"+f"(d[14]),"+f"(d[15]),"+f"(d[16]),"+f"(d[17]),"+f"(d[18]),"+f"(d[19]),"+f"(d[20]),"+f"(d[21]),"+f"(d[22]),"+f"(d[23]),"+f"(d[24]),"+f"(d[25]),"+f"(d[26]),"+f"(d[27]),"+f"(d[28]),"+f"(d[29]),"+f"(d[30]),"+f"(d[31]),"+f"(d[32]),"+f"(d[33]),"+f"(d[34]),"+f"(d[35]),"+f"(d[36]),"+f"(d[37]),"+f"(d[38]),"+f"(d[39]),"+f"(d[40]),"+f"(d[41]),"+f"(d[42]),"+f"(d[43]),"+f"(d[44]),"+f"(d[45]),"+f"(d[46]),"+f"(d[47]),"+f"(d[48]),"+f"(d[49]),"+f"(d[50]),"+f"(d[51]),"+f"(d[52]),"+f"(d[53]),"+f"(d[54]),"+f"(d[55]),"+f"(d[56]),"+f"(d[57]),"+f"(d[58]),"+f"(d[59]),"+f"(d[60]),"+f"(d[61]),"+f"(d[62]),"+f"(d[63])
    : "l"(descA), "l"(descB), "r"(scaleD));
}
__device__ __forceinline__ void wgmma_ss_n40(float* d, uint64_t descA, uint64_t descB, int scaleD) {
  asm volatile("{\n.reg .pred p;\nsetp.ne.b32 p, %22, 0;\n"
    "wgmma.mma_async.sync.aligned.m64n40k16.f32.bf16.bf16 {%0,%1,%2,%3,%4,%5,%6,%7,%8,%9,%10,%11,%12,%13,%14,%15,%16,%17,%18,%19}, %20, %21, p, 1, 1, 0, 0;\n}\n"
    : "+f"(d[0]),"+f"(d[1]),"+f"(d[2]),"+f"(d[3]),"+f"(d[4]),"+f"(d[5]),"+f"(d[6]),"+f"(d[7]),"+f"(d[8]),"+f"(d[9]),"+f"(d[10]),"+f"(d[11]),"+f"(d[12]),"+f"(d[13]),"+f"(d[14]),"+f"(d[15]),"+f"(d[16]),"+f"(d[17]),"+f"(d[18]),"+f"(d[19])
    : "l"(descA), "l"(descB), "r"(scaleD));
}
__device__ __forceinline__ void wgmma_ss_n32_ta(float* d, uint64_t descA, uint64_t descB, int scaleD) {
  asm volatile("{\n.reg .pred p;\nsetp.ne.b32 p, %18, 0;\n"
    "wgmma.mma_async.sync.aligned.m64n32k16.f32.bf16.bf16 {%0,%1,%2,%3,%4,%5,%6,%7,%8,%9,%10,%11,%12,%13,%14,%15}, %16, %17, p, 1, 1, 1, 0;\n}\n"
    : "+f"(d[0]),"+f"(d[1]),"+f"(d[2]),"+f"(d[3]),"+f"(d[4]),"+f"(d[5]),"+f"(d[6]),"+f"(d[7]),"+f"(d[8]),"+f"(d[9]),"+f"(d[10]),"+f"(d[11]),"+f"(d[12]),"+f"(d[13]),"+f"(d[14]),"+f"(d[15])
    : "l"(descA), "l"(descB), "r"(scaleD));
}
struct ChainArgs {
  const bf16* mem0;
  uint32_t* Mg;
  float4* Sg;
  uint32_t* flag;
  uint32_t* dbg;
};

constexpr int XT_BYTES = 28672;
constexpr int STG_BYTES = 5120;
constexpr int OFF_A = 0, OFF_B = 65536, OFF_C = OFF_B + 3 * XT_BYTES, OFF_M = OFF_C + 2 * XT_BYTES, OFF_P = OFF_M + 2 * 7168,
              OFF_SX = OFF_P + 4096, OFF_SM = OFF_SX + 2048, OFF_SW = OFF_SM + 512, OFF_BAR = OFF_SW + 1024, OFF_DBG = OFF_B + 2 * XT_BYTES + 3 * 7168, SMEM_CHAIN = OFF_BAR + 512;
enum { B_PA = 0, B_PE = 1, B_XF = 4, B_MB = 9, B_SX = 11, B_SM = 13, B_PB = 15, B_KR = 17, B_ST = 21, B_PF = 29, B_RD = 45, B_MF = 47, B_EM = 51, B_SB = 55, B_PE5 = 56, B_NUM = 61 };
#define MREP 4
#define MD0 250
#define MDELTA 900
#define SSTART 800
#define SXSTART 500
#define SSTAG 130
constexpr float L2E = 1.4426950408889634f;
constexpr int CHAIN_THREADS = 512;
#define TOKK 28

__device__ __forceinline__ uint32_t xstage_off(int st) { return st < 2 ? OFF_C + st * XT_BYTES : OFF_B + (st - 2) * XT_BYTES; }
__device__ __forceinline__ uint32_t mslot_off(int k) { return k < 3 ? OFF_B + 2 * XT_BYTES + k * 7168 : OFF_M; }
constexpr int OFF_VAR = OFF_BAR + 496;

__device__ __forceinline__ bool slot_has_sentinel(const uint8_t* p, int lane) {
  bool bad = false;
#pragma unroll 2
  for (int i = 0; i < 14; i++) { const uint4 v = *reinterpret_cast<const uint4*>(p + (32 * i + lane) * 16); bad |= (v.x == ~0u) | (v.y == ~0u) | (v.z == ~0u) | (v.w == ~0u); }
  return __any_sync(~0u, bad);
}
__device__ __forceinline__ uint32_t clk32() { uint32_t c; asm volatile("mov.u32 %0, %%clock;" : "=r"(c)); return c; }
__device__ __forceinline__ void wait_until(uint32_t t, uint32_t saddr) {
  while ((int)(clk32() - t) < 0) { uint32_t d; asm volatile("ld.volatile.shared.u32 %0, [%1];" : "=r"(d) : "r"(saddr) : "memory"); asm volatile("" ::"r"(d)); if (d == 0x12345u) break; }
}
#define DBG(slot) do {} while (0)
#define DBGV(slot, v) do {} while (0)

#define PDBG(i) do {} while (0)

template <bool CL>
__device__ __forceinline__ void issue_x_load(uint32_t sb, const CUtensorMap* tm_x, const CUtensorMap* tm_x3, int seg, int rank) {
  const int st = seg & 3;
  const uint32_t bar = sb + OFF_BAR + (B_XF + st) * 8;
  const uint32_t dst = sb + xstage_off(st);
  mbar_expect_tx(bar, XT_BYTES);
  if (CL) {
    if (rank < NJ) tma_load_2d_mc(dst + rank * 4096, tm_x, rank * 64, seg * SEG, bar, (uint16_t)0xFFFF);
  } else {
    tma_load_3d(dst, tm_x3, 0, seg * SEG, 0, bar);
  }
}

template <int WG>
__device__ __forceinline__ void tile_prologue(uint32_t* W, uint32_t sb) {
  const uint32_t bar = sb + OFF_BAR;
  const int lane = threadIdx.x & 31;
  float acc[112];
  mbar_wait(bar + B_PA * 8, 0);
#pragma unroll
  for (int half = 0; half < 2; half++) {
#pragma unroll
    for (int ec = 0; ec < 4; ec++) {
      const int i = half * 8 + ec * 2 + WG;
      const int st = i % 5;
      mbar_wait(bar + (B_PF + i) * 8, 0);
      const uint32_t bb = sb + OFF_B + st * XT_BYTES;
      wg_fence();
#pragma unroll
      for (int kk = 0; kk < 4; kk++) {
        if (WG == 0) {
          wgmma_ss_n112(acc, desc_sw128(sb + OFF_A + ec * 8192 + kk * 32), desc_sw128(bb + kk * 32), (ec | kk) != 0);
          wgmma_ss_n112(acc + 56, desc_sw128(sb + OFF_A + ec * 8192 + kk * 32), desc_sw128(bb + 14336 + kk * 32), (ec | kk) != 0);
        } else {
          wgmma_ss_n112_ta(acc, desc_sw128(sb + OFF_A + 32768 + (ec * 64 + kk * 16) * 128), desc_sw128(bb + kk * 32), (ec | kk) != 0);
          wgmma_ss_n112_ta(acc + 56, desc_sw128(sb + OFF_A + 32768 + (ec * 64 + kk * 16) * 128), desc_sw128(bb + 14336 + kk * 32), (ec | kk) != 0);
        }
      }
      wg_commit();
      wg_wait<0>();
      if (lane == 0) mbar_arrive(bar + (B_PE5 + st) * 8);
    }
    const float sc = WG == 0 ? 0.0625f : 1.0f;
#pragma unroll
    for (int kk = 0; kk < 14; kk++) {
      W[half * 56 + kk * 4 + 0] = pack_bf16(acc[8 * kk + 0] * sc, acc[8 * kk + 1] * sc);
      W[half * 56 + kk * 4 + 1] = pack_bf16(acc[8 * kk + 2] * sc, acc[8 * kk + 3] * sc);
      W[half * 56 + kk * 4 + 2] = pack_bf16(acc[8 * kk + 4] * sc, acc[8 * kk + 5] * sc);
      W[half * 56 + kk * 4 + 3] = pack_bf16(acc[8 * kk + 6] * sc, acc[8 * kk + 7] * sc);
    }
  }
}

__device__ __forceinline__ void token_gemm(const uint32_t* W, uint32_t sb, int seg, uint32_t stg_base, int w, int lane) {
  const int st = seg & 3;
  mbar_wait(sb + OFF_BAR + (B_XF + st) * 8, (seg >> 2) & 1);
  const uint32_t xb = sb + xstage_off(st);
  float d[16];
  wg_fence();
#pragma unroll
  for (int kk = 0; kk < TOKK; kk++) wgmma_rs_n32(d, &W[4 * kk], desc_sw128(xb + (kk >> 2) * 4096 + (kk & 3) * 32), kk != 0);
  wg_commit();
  wg_wait<0>();
  const uint32_t stg = stg_base + (seg & 3) * STG_BYTES + 1024;
  const int r = lane & 7, mi = lane >> 3;
#pragma unroll
  for (int p = 0; p < 2; p++) {
    const int t = 8 * (2 * p + (mi >> 1)) + r;
    const int chunk = 2 * w + (mi & 1);
    const uint32_t addr = stg + t * 128 + ((chunk ^ r) << 4);
    stsm_x4_t(addr, pack_bf16(d[8 * p + 0], d[8 * p + 1]), pack_bf16(d[8 * p + 2], d[8 * p + 3]), pack_bf16(d[8 * p + 4], d[8 * p + 5]),
              pack_bf16(d[8 * p + 6], d[8 * p + 7]));
  }
}

__device__ __forceinline__ void poll_smm(uint8_t* smem, uint32_t bar, const float4* src, int s, int p, int lane) {
  volatile uint32_t* var = reinterpret_cast<volatile uint32_t*>(smem + OFF_VAR);
  { int it = 0; while (var[1] != (uint32_t)s && ++it < SPIN_LIMIT) __nanosleep(20); }
  const uint32_t tM = clk32();
  wait_until(tM + SSTART + p * SSTAG, bar - OFF_BAR + OFF_VAR + 12);
  uint4 v; int it = 0; bool mine = true;
  while (true) {
    v = ld_vol_v4(src);
    if (__all_sync(~0u, __uint_as_float(v.z) == 7.f)) break;
    if (mbar_test(bar + (B_SM + (s & 1)) * 8, (s >> 1) & 1)) { mine = false; break; }
    if (++it > SPIN_LIMIT) break;
  }
  if (mine) {
    reinterpret_cast<float2*>(smem + OFF_SM + (s & 1) * 256)[lane] = make_float2(__uint_as_float(v.x), __uint_as_float(v.y));
    __syncwarp();
    if (lane == 0) { if (atomicExch(reinterpret_cast<uint32_t*>(smem + OFF_VAR), (uint32_t)(s + 1)) != (uint32_t)(s + 1)) mbar_arrive(bar + (B_SM + (s & 1)) * 8); }
  }
}

template <bool CL>
__global__ void __launch_bounds__(CHAIN_THREADS, 1)
chain_kernel(const __grid_constant__ CUtensorMap tm_x, const __grid_constant__ CUtensorMap tm_wq, const __grid_constant__ CUtensorMap tm_wk,
             const __grid_constant__ CUtensorMap tm_wv, const __grid_constant__ CUtensorMap tm_wo, const __grid_constant__ CUtensorMap tm_k,
             const __grid_constant__ CUtensorMap tm_y, const __grid_constant__ CUtensorMap tm_x3, ChainArgs args) {
  extern __shared__ __align__(1024) uint8_t smem[];
  const uint32_t sb = smem_u32(smem);
  const int tid = threadIdx.x, warp = tid >> 5, lane = tid & 31;
  const int j = blockIdx.x >> 4, h = blockIdx.x & 15;
  const uint32_t bar = sb + OFF_BAR;
  const int g = lane >> 2, q = lane & 3;
  KT_START(0);

  if (tid == 0) {
    mbar_init(bar + B_PA * 8, 1);
    for (int i = 0; i < 5; i++) mbar_init(bar + (B_PE5 + i) * 8, 4);
    for (int i = 0; i < 16; i++) mbar_init(bar + (B_PF + i) * 8, 1);
    for (int i = 0; i < 5; i++) mbar_init(bar + (B_XF + i) * 8, 1);
    for (int i = 0; i < 2; i++) {
      mbar_init(bar + (B_SX + i) * 8, 4); mbar_init(bar + (B_SM + i) * 8, 1); mbar_init(bar + (B_PB + i) * 8, 1); mbar_init(bar + (B_RD + i) * 8, 1);
    }
    for (int i = 0; i < 4; i++) { mbar_init(bar + (B_KR + i) * 8, 4); mbar_init(bar + (B_MF + i) * 8, 1); mbar_init(bar + (B_EM + i) * 8, 4); }
    mbar_init(bar + B_SB * 8, 1);
    for (int i = 0; i < 8; i++) mbar_init(bar + (B_ST + i) * 8, 4);
    asm volatile("fence.mbarrier_init.release.cluster;" ::: "memory");
  }
  __syncthreads();
  if (CL) cluster_sync_all();
  asm volatile("griddepcontrol.launch_dependents;" ::: "memory");
  PDBG(0);

  const int wgi = __shfl_sync(0xffffffffu, tid >> 7, 0);
  if (wgi < 2) {
    asm volatile("setmaxnreg.inc.sync.aligned.u32 200;");
    const int wg = wgi, w = warp & 3;
    uint32_t W[112];
    mbar_wait(bar + B_PA * 8, 0);
    PDBG(1);
    mbar_wait(bar + B_PF * 8, 0);
    PDBG(2);
    if (wg == 0) tile_prologue<0>(W, sb); else tile_prologue<1>(W, sb);
    PDBG(3);
    named_bar(0, CHAIN_THREADS);
    PDBG(4);
    PDBG(5);

    const uint32_t stg_base = sb + OFF_A + wg * 4 * STG_BYTES;
    token_gemm(W, sb, 0, stg_base, w, lane);
    PDBG(6);
    PDBG(7);
    __syncwarp();
    if (wg == 0 && lane == 0) mbar_arrive(bar + (B_KR + 0) * 8);

    if (wg == 0) {
      for (int s = 0; s < NSEG; s++) {
        float d0, d1, d2, d3;
        uint32_t ma[2];
        volatile uint32_t* var = reinterpret_cast<volatile uint32_t*>(smem + OFF_VAR);
        mbar_wait(bar + B_SB * 8, s & 1);
        uint32_t n = var[3];
        const uint32_t n_first = n;
        while (true) {
          const int slot = n & 3;
          mbar_wait(bar + (B_MF + slot) * 8, (n >> 2) & 1);
          if (tid == 0) DBG(0);
          const uint32_t ms = sb + mslot_off(slot);
          float a4[4][4];
#pragma unroll
          for (int i = 0; i < 4; i++) { a4[i][0] = a4[i][1] = a4[i][2] = a4[i][3] = 0.f; }
          uint32_t b[14][4];
#pragma unroll
          for (int i = 0; i < 14; i++) ldsm_x4_t(b[i], ms + (32 * i + lane) * 16);
          ldsm_x2_t(ma, ms + (64 * j + 16 * w + (lane & 15)) * 16);
#pragma unroll
          for (int i = 0; i < 14; i++) {
            mma16816(a4[(2 * i) & 3], W[8 * i + 0], W[8 * i + 1], W[8 * i + 2], W[8 * i + 3], b[i][0], b[i][1]);
            mma16816(a4[(2 * i + 1) & 3], W[8 * i + 4], W[8 * i + 5], W[8 * i + 6], W[8 * i + 7], b[i][2], b[i][3]);
          }
          d0 = (a4[0][0] + a4[1][0]) + (a4[2][0] + a4[3][0]); d1 = (a4[0][1] + a4[1][1]) + (a4[2][1] + a4[3][1]);
          d2 = (a4[0][2] + a4[1][2]) + (a4[2][2] + a4[3][2]); d3 = (a4[0][3] + a4[1][3]) + (a4[2][3] + a4[3][3]);
          if (!__any_sync(~0u, (d0 != d0) | (d1 != d1))) break;
          if (!slot_has_sentinel(smem + mslot_off(slot), lane)) break;
          if (n - n_first > (uint32_t)SPIN_LIMIT) break;
          if (lane == 0) mbar_arrive(bar + (B_EM + slot) * 8);
          n++;
        }
        if (tid == 0) { var[2] = n; var[1] = s; DBGV(14, n - n_first); }
        asm volatile("bar.arrive 5, 256;" ::: "memory");
        if (tid == 0) { asm volatile("" :: "f"(d0), "f"(d3)); DBG(8); }
        const uint32_t kb0 = movm_t(pack_bf16(d0, d1)), kb1 = movm_t(pack_bf16(d2, d3));
        if (s < NSEG - 1) {
          float c[4] = {0.f, 0.f, 0.f, 0.f};
          mma16816(c, ma[0], 0u, ma[1], 0u, kb0, kb1);
          float2* sw = reinterpret_cast<float2*>(smem + OFF_SW);
          sw[w * 32 + lane] = make_float2(c[0], c[1]);
          if (tid == 0) DBG(9);
          named_bar(1, 128);
          if (tid == 0) DBG(10);
          if (w == 0) {
            const float2 v0 = sw[lane], v1 = sw[32 + lane], v2 = sw[64 + lane], v3 = sw[96 + lane];
            red_v4(args.Sg + (((size_t)s * NH + h) * 5 + 4) * 32 + lane, (v0.x + v1.x) + (v2.x + v3.x), (v0.y + v1.y) + (v2.y + v3.y), 1.f, 0.f);
          }
        }
        asm volatile("bar.arrive 3, 256;" ::: "memory");
        if (tid == 0) DBG(1);
        {
          const uint32_t stg = stg_base + (s & 3) * STG_BYTES + g * 128 + q * 4;
          asm volatile("st.shared.u32 [%0], %1;" ::"r"(stg + (((2 * w) ^ g) << 4)), "r"(kb0) : "memory");
          asm volatile("st.shared.u32 [%0], %1;" ::"r"(stg + (((2 * w + 1) ^ g) << 4)), "r"(kb1) : "memory");
          fence_async_smem();
          __syncwarp();
          if (lane == 0) mbar_arrive(bar + (B_ST + (s & 3)) * 8);
        }
        if (s + 1 < NSEG) {
          token_gemm(W, sb, s + 1, stg_base, w, lane);
          __syncwarp();
          if (lane == 0) mbar_arrive(bar + (B_KR + ((s + 1) & 3)) * 8);
        }
        if (tid == 0) DBG(11);
        named_bar(1, 128);
      }
    } else {
      const int hd = w * 4 + (lane >> 3);
      uint32_t p_dst = sb + OFF_P + h * 128 + (lane & 7) * 16, p_bar = bar + B_PB * 8;
      if (CL) { p_dst = mapa(p_dst, hd); p_bar = mapa(p_bar, hd); }
      const uint32_t ONE2 = 0x3F803F80u;
      for (int s = 0; s < NSEG; s++) {
        if (s < NSEG - 1) {
          mbar_wait(bar + (B_KR + (s & 3)) * 8, (s >> 2) & 1);
          const uint32_t kst = sb + OFF_A + (s & 3) * STG_BYTES + 1024;
          uint32_t bk[2][4];
#pragma unroll
          for (int i = 0; i < 2; i++) ldsm_x4(bk[i], kst + (8 * w + (lane & 7)) * 128 + (((4 * i + (lane >> 3)) ^ (lane & 7)) << 4));
          float c[4], c2[4];
          volatile uint32_t* var = reinterpret_cast<volatile uint32_t*>(smem + OFF_VAR);
          mbar_wait(bar + B_SB * 8, s & 1);
          uint32_t n = var[3];
          mbar_wait(bar + (B_MF + (n & 3)) * 8, (n >> 2) & 1);
          bool synced = false;
          while (true) {
            const uint32_t ms = sb + mslot_off(n & 3);
            c[0] = c[1] = c[2] = c[3] = 0.f; c2[0] = c2[1] = c2[2] = c2[3] = 0.f;
            uint32_t a[2][4];
            ldsm_x4_t(a[0], ms + (64 * j + lane) * 16);
            ldsm_x4_t(a[1], ms + (64 * j + 32 + lane) * 16);
            mma16816(c, a[0][0], 0u, a[0][1], 0u, bk[0][0], bk[0][1]);
            mma16816(c2, a[0][2], 0u, a[0][3], 0u, bk[0][2], bk[0][3]);
            mma16816(c, a[1][0], 0u, a[1][1], 0u, bk[1][0], bk[1][1]);
            mma16816(c2, a[1][2], 0u, a[1][3], 0u, bk[1][2], bk[1][3]);
            c[0] += c2[0]; c[1] += c2[1];
            if (synced || !__any_sync(~0u, (c[0] != c[0]) | (c[1] != c[1]))) break;
            named_bar(5, 256);
            synced = true;
            n = var[2];
          }
          red_v4(args.Sg + (((size_t)s * NH + h) * 5 + w) * 32 + lane, c[0], c[1], 1.f, 0.f);
          if (!synced) named_bar(5, 256);
        } else named_bar(5, 256);
        named_bar(3, 256);
        const uint32_t ms = sb + mslot_off(reinterpret_cast<volatile uint32_t*>(smem + OFF_VAR)[2] & 3);
        float a4[4][4];
#pragma unroll
        for (int i = 0; i < 4; i++) { a4[i][0] = a4[i][1] = a4[i][2] = a4[i][3] = 0.f; }
        {
          uint32_t b[14][4];
#pragma unroll
          for (int i = 0; i < 14; i++) ldsm_x4_t(b[i], ms + (32 * i + lane) * 16);
#pragma unroll
          for (int i = 0; i < 14; i++) {
            mma16816(a4[(2 * i) & 3], W[8 * i + 0], W[8 * i + 1], W[8 * i + 2], W[8 * i + 3], b[i][0], b[i][1]);
            mma16816(a4[(2 * i + 1) & 3], W[8 * i + 4], W[8 * i + 5], W[8 * i + 6], W[8 * i + 7], b[i][2], b[i][3]);
          }
        }
        const uint32_t za0 = pack_bf16((a4[0][0] + a4[1][0]) + (a4[2][0] + a4[3][0]), (a4[0][1] + a4[1][1]) + (a4[2][1] + a4[3][1]));
        const uint32_t za1 = pack_bf16((a4[0][2] + a4[1][2]) + (a4[2][2] + a4[3][2]), (a4[0][3] + a4[1][3]) + (a4[2][3] + a4[3][3]));
        {
          const uint32_t stg = stg_base + (s & 3) * STG_BYTES + g * 128 + q * 4;
          asm volatile("st.shared.u32 [%0], %1;" ::"r"(stg + (((2 * w) ^ g) << 4)), "r"(movm_t(za0)) : "memory");
          asm volatile("st.shared.u32 [%0], %1;" ::"r"(stg + (((2 * w + 1) ^ g) << 4)), "r"(movm_t(za1)) : "memory");
          fence_async_smem();
          __syncwarp();
          if (lane == 0) mbar_arrive(bar + (B_ST + 4 + (s & 3)) * 8);
        }
        if (s < NSEG - 1) {
          uint32_t va[2][4];
          const uint32_t vst = stg_base + (s & 3) * STG_BYTES + 1024;
#pragma unroll
          for (int kk = 0; kk < 2; kk++) {
            const int mi = lane >> 3, r = lane & 7;
            const int t = 8 * (2 * kk + (mi >> 1)) + r;
            ldsm_x4_t(va[kk], vst + t * 128 + (((2 * w + (mi & 1)) ^ r) << 4));
          }
          mbar_wait(bar + (B_SX + (s & 1)) * 8, (s >> 1) & 1);
          const float2* sx = reinterpret_cast<const float2*>(smem + OFF_SX + (s & 1) * 1024);
          float ex[8];
#pragma unroll
          for (int nt = 0; nt < 4; nt++) { const float2 v = sx[nt * 32 + lane]; ex[2 * nt] = v.x; ex[2 * nt + 1] = v.y; }
          float mx = fmaxf(fmaxf(fmaxf(ex[0], ex[1]), fmaxf(ex[2], ex[3])), fmaxf(fmaxf(ex[4], ex[5]), fmaxf(ex[6], ex[7])));
          mx = fmaxf(mx, __shfl_xor_sync(~0u, mx, 1));
          mx = fmaxf(mx, __shfl_xor_sync(~0u, mx, 2));
#pragma unroll
          for (int k = 0; k < 8; k++) ex[k] = ex2((ex[k] - mx) * L2E);
          mbar_wait(bar + (B_SM + (s & 1)) * 8, (s >> 1) & 1);
          if (tid == 128) DBG(2);
          const float2 sm = reinterpret_cast<const float2*>(smem + OFF_SM + (s & 1) * 256)[lane];
          float mm = fmaxf(sm.x, sm.y);
          mm = fmaxf(mm, __shfl_xor_sync(~0u, mm, 1));
          mm = fmaxf(mm, __shfl_xor_sync(~0u, mm, 2));
          const float m = fmaxf(mx, mm);
          const float f = ex2((mx - m) * L2E);
          const uint32_t pm = pack_bf16(ex2((sm.x - m) * L2E), ex2((sm.y - m) * L2E));
          uint32_t bx[4];
#pragma unroll
          for (int nt = 0; nt < 4; nt++) bx[nt] = pack_bf16(ex[2 * nt] * f, ex[2 * nt + 1] * f);
          float o0[4] = {0.f, 0.f, 0.f, 0.f}, o1[4] = {0.f, 0.f, 0.f, 0.f}, o2[4] = {0.f, 0.f, 0.f, 0.f};
          float l0[4] = {0.f, 0.f, 0.f, 0.f}, l1[4] = {0.f, 0.f, 0.f, 0.f}, l2[4] = {0.f, 0.f, 0.f, 0.f};
          mma1688(o0, za0, za1, pm);
          mma1688(l0, ONE2, ONE2, pm);
          mma16816(o1, va[0][0], va[0][1], va[0][2], va[0][3], bx[0], bx[1]);
          mma16816(l1, ONE2, ONE2, ONE2, ONE2, bx[0], bx[1]);
          mma16816(o2, va[1][0], va[1][1], va[1][2], va[1][3], bx[2], bx[3]);
          mma16816(l2, ONE2, ONE2, ONE2, ONE2, bx[2], bx[3]);
          const float r0 = __fdividef(1.f, l0[0] + l1[0] + l2[0]), r1 = __fdividef(1.f, l0[1] + l1[1] + l2[1]);
          const float v0 = (o0[0] + o1[0] + o2[0]) * r0, v1 = (o0[1] + o1[1] + o2[1]) * r1;
          const float v2 = (o0[2] + o1[2] + o2[2]) * r0, v3 = (o0[3] + o1[3] + o2[3]) * r1;
          if (CL) {
            st_async_v4(p_dst + (s & 1) * 2048, v0, v1, v2, v3, p_bar + (s & 1) * 8);
          } else {
            uint4* dst = reinterpret_cast<uint4*>(args.Sg + (size_t)NSEG * NH * 5 * 32) + ((((size_t)s * NJ + j) * 16 + hd) * 16 + h) * 8 + (lane & 7);
            uint32_t u0 = ~__float_as_uint(v0), u1 = ~__float_as_uint(v1), u2 = ~__float_as_uint(v2), u3 = ~__float_as_uint(v3);
            u0 += (u0 == 0); u1 += (u1 == 0); u2 += (u2 == 0); u3 += (u3 == 0);
            asm volatile("st.relaxed.gpu.global.v4.u32 [%0], {%1,%2,%3,%4};" ::"l"(dst), "r"(u0), "r"(u1), "r"(u2), "r"(u3) : "memory");
          }
          if (tid == 128) DBG(3);
        }
        if (s + 1 < NSEG) token_gemm(W, sb, s + 1, stg_base, w, lane);
        if (tid == 128) DBG(12);
      }
    }
  } else if (wgi == 2) {
    asm volatile("setmaxnreg.dec.sync.aligned.u32 80;");
    const int aw = warp - 8, at = tid - 256;
    named_bar(0, CHAIN_THREADS);
    for (int s = 0; s < NSEG; s++) {
      volatile uint32_t* var = reinterpret_cast<volatile uint32_t*>(smem + OFF_VAR);
      if (s == 0) {
        for (int c = at; c < DM; c += 128) {
          uint32_t v[4];
#pragma unroll
          for (int i = 0; i < 4; i++) {
            uint32_t lo = reinterpret_cast<const uint16_t*>(args.mem0)[(2 * i) * DM + c], hi = reinterpret_cast<const uint16_t*>(args.mem0)[(2 * i + 1) * DM + c];
            if (lo == 0xFFFFu) lo = 0x7FFFu;
            if (hi == 0xFFFFu) hi = 0x7FFFu;
            v[i] = lo | (hi << 16);
          }
          *reinterpret_cast<uint4*>(smem + mslot_off(0) + c * 16) = make_uint4(v[0], v[1], v[2], v[3]);
        }
        fence_async_smem();
        named_bar(2, 128);
        if (at == 0) mbar_arrive(bar + B_MF * 8);
      }
      { int it = 0; while (var[1] != (uint32_t)s && ++it < SPIN_LIMIT) __nanosleep(20); }
      if (j == 0) {
        const float4 z4 = make_float4(0.f, 0.f, 0.f, 0.f);
        if (s >= 2) { float4* p = args.Sg + ((size_t)(s - 2) * NH + h) * 160; p[aw * 32 + lane] = z4; if (aw == 0) p[128 + lane] = z4; }
        if (s == NSEG - 1) { float4* p = args.Sg + ((size_t)(s - 1) * NH + h) * 160; p[aw * 32 + lane] = z4; if (aw == 0) p[128 + lane] = z4; }
      }
      if (at == 32) DBG(4);
      if (s == NSEG - 1) break;
      const uint32_t tM = clk32();
      {
        const float4* src = args.Sg + (((size_t)s * NH + h) * 5 + aw) * 32 + lane;
        wait_until(tM + SXSTART, sb + OFF_VAR + 12);
        uint4 v; int it = 0;
        do { v = ld_vol_v4(src); } while (__uint_as_float(v.z) != 7.f && ++it < SPIN_LIMIT);
        reinterpret_cast<float2*>(smem + OFF_SX + (s & 1) * 1024)[aw * 32 + lane] = make_float2(__uint_as_float(v.x), __uint_as_float(v.y));
        __syncwarp();
        if (lane == 0) mbar_arrive(bar + (B_SX + (s & 1)) * 8);
        if (at == 0) DBG(13);
      }
    }
  } else {
    asm volatile("setmaxnreg.dec.sync.aligned.u32 32;");
    if (tid == 384) {
      reinterpret_cast<uint32_t*>(smem + OFF_VAR)[0] = 0; reinterpret_cast<uint32_t*>(smem + OFF_VAR)[1] = ~0u;
      mbar_expect_tx(bar + B_PA * 8, 65536);
#pragma unroll
      for (int ec = 0; ec < 4; ec++) tma_load_2d(sb + OFF_A + ec * 8192, &tm_wq, h * DH + ec * 64, 64 * j, bar + B_PA * 8);
      tma_load_2d(sb + OFF_A + 32768, &tm_wo, 64 * j, h * DH, bar + B_PA * 8);
      for (int i = 0; i < 16; i++) {
        const int st = i % 5, half = i >> 3, ec = (i & 7) >> 1;
        if (i >= 5) mbar_wait(bar + (B_PE5 + st) * 8, ((i / 5) - 1) & 1);
        mbar_expect_tx(bar + (B_PF + i) * 8, XT_BYTES);
        tma_load_2d(sb + OFF_B + st * XT_BYTES, (i & 1) ? &tm_wv : &tm_wk, h * DH + ec * 64, half * 224, bar + (B_PF + i) * 8);
      }
    }
    if (tid == 384) {
#pragma unroll 1
      for (int sg = 0; sg < 2; sg++) {
        mbar_wait(bar + (B_PE5 + 3 + sg) * 8, 0);
        mbar_expect_tx(bar + (B_XF + sg) * 8, XT_BYTES);
        tma_load_3d(sb + xstage_off(sg), &tm_x3, 0, sg * SEG, 0, bar + (B_XF + sg) * 8);
      }
    }
    if (warp == 13 && !(lane & 1)) {
      const int l8 = lane >> 2, v = lane & 3;
      const int c = 16 * (h >> 2) + 2 * (h & 3) + (l8 >> 2) + (v >> 1) * 8;
      for (int s = 1; s < NSEG; s++)
#pragma unroll
        for (int r = 0; r < MREP; r++) st_relaxed(args.Mg + ((size_t)s * MREP + r) * 1792 + (64 * j + c) * 4 + (l8 & 3), 0xFFFFFFFFu);
      __threadfence();
    }
    __syncwarp();
    named_bar(0, CHAIN_THREADS);
    if (tid == 384) {
      issue_x_load<false>(sb, &tm_x, &tm_x3, 2, h);
      for (int s = 0; s < NSEG; s++) {
        mbar_wait(bar + (B_ST + (s & 3)) * 8, (s >> 2) & 1);
        tma_store_2d(&tm_k, 64 * j, (h * NSEG + s) * LKEY, sb + OFF_A + (s & 3) * STG_BYTES);
        mbar_wait(bar + (B_ST + 4 + (s & 3)) * 8, (s >> 2) & 1);
        tma_store_2d(&tm_y, 64 * j, (h * NSEG + s) * LKEY, sb + OFF_A + (4 + (s & 3)) * STG_BYTES);
        bulk_commit();
        if (s + 3 < NSEG) { if (s == 0) issue_x_load<false>(sb, &tm_x, &tm_x3, 3, h); else issue_x_load<CL>(sb, &tm_x, &tm_x3, s + 3, h); }
        bulk_wait<0>();
        fence_async_all();
        __threadfence();
        red_u32(args.flag + s, 1u);
      }
    } else if (warp == 13) {
      for (int s = 0; s < NSEG - 1; s++) {
        float acc;
        if (CL && lane == 0) mbar_expect_tx(bar + (B_PB + (s & 1)) * 8, 16 * 128);
        poll_smm(smem, bar, args.Sg + (((size_t)s * NH + h) * 5 + 4) * 32 + lane, s, 1, lane);
        if (CL) {
          mbar_wait_cluster(bar + (B_PB + (s & 1)) * 8, (s >> 1) & 1);
          if (lane == 0) DBG(5);
          const float* pin = reinterpret_cast<const float*>(smem + OFF_P + (s & 1) * 2048);
          float a0 = 0.f, a1 = 0.f, a2 = 0.f, a3 = 0.f;
#pragma unroll
          for (int k = 0; k < 16; k += 4) { a0 += pin[k * 32 + lane]; a1 += pin[(k + 1) * 32 + lane]; a2 += pin[(k + 2) * 32 + lane]; a3 += pin[(k + 3) * 32 + lane]; }
          acc = (a0 + a1) + (a2 + a3);
        } else {
          const uint32_t* src = reinterpret_cast<const uint32_t*>(args.Sg + (size_t)NSEG * NH * 5 * 32) + (((size_t)s * NJ + j) * 16 + h) * 16 * 32 + lane;
          acc = 0.f;
#pragma unroll 1
          for (int k = 0; k < 16; k += 4) {
            uint32_t v0, v1, v2, v3; int it = 0;
            do {
              asm volatile("ld.volatile.global.u32 %0, [%1];" : "=r"(v0) : "l"(src + k * 32) : "memory");
              asm volatile("ld.volatile.global.u32 %0, [%1];" : "=r"(v1) : "l"(src + k * 32 + 32) : "memory");
              asm volatile("ld.volatile.global.u32 %0, [%1];" : "=r"(v2) : "l"(src + k * 32 + 64) : "memory");
              asm volatile("ld.volatile.global.u32 %0, [%1];" : "=r"(v3) : "l"(src + k * 32 + 96) : "memory");
            } while ((v0 == 0u || v1 == 0u || v2 == 0u || v3 == 0u) && ++it < SPIN_LIMIT);
            acc += (__uint_as_float(~v0) + __uint_as_float(~v1)) + (__uint_as_float(~v2) + __uint_as_float(~v3));
            uint32_t* cl = const_cast<uint32_t*>(src) + k * 32;
            cl[0] = 0u; cl[32] = 0u; cl[64] = 0u; cl[96] = 0u;
          }
        }
        const float o = __shfl_down_sync(~0u, acc, 1);
        const uint32_t u = pack_bf16(acc, o);
        const int l8 = lane >> 2, v = lane & 3;
        const int c = 16 * (h >> 2) + 2 * (h & 3) + (l8 >> 2) + (v >> 1) * 8;
        if (!(lane & 1)) {
#pragma unroll
          for (int r = 0; r < MREP; r++) st_relaxed(args.Mg + ((size_t)(s + 1) * MREP + r) * 1792 + (64 * j + c) * 4 + (l8 & 3), u);
        }
        if (lane == 0) { DBG(6); mbar_arrive(bar + (B_RD + (s & 1)) * 8); }
      }
    } else if (warp == 15) {
      for (int s = 0; s < NSEG - 1; s++) poll_smm(smem, bar, args.Sg + (((size_t)s * NH + h) * 5 + 4) * 32 + lane, s, 0, lane);
    } else if (tid == 448) {
      volatile uint32_t* var = reinterpret_cast<volatile uint32_t*>(smem + OFF_VAR);
      uint32_t n = 0, empar = 0;
      for (int s = 0; s < NSEG; s++) {
        if (s > 0) mbar_wait(bar + (B_RD + ((s - 1) & 1)) * 8, ((s - 1) >> 1) & 1);
        const uint32_t n0 = n;
        var[3] = n0;
        mbar_arrive(bar + B_SB * 8);
        uint32_t tnext = clk32() + MD0;
        int it = 0;
        if (s == 0) n = 1;
        while (s > 0) {
          bool done = false;
          while ((int)(clk32() - tnext) < 0) { if (var[1] == (uint32_t)s) { done = true; break; } }
          if (done || var[1] == (uint32_t)s || ++it > SPIN_LIMIT) break;
          const int slot = n & 3;
          if (n - n0 >= 4) {
            int it2 = 0;
            while (!mbar_test(bar + (B_EM + slot) * 8, (empar >> slot) & 1)) { if (var[1] == (uint32_t)s || ++it2 > SPIN_LIMIT) { done = true; break; } }
            if (done) break;
            empar ^= 1u << slot;
          }
          mbar_expect_tx(bar + (B_MF + slot) * 8, 7168);
          bulk_load(sb + mslot_off(slot), args.Mg + ((size_t)s * MREP + (blockIdx.x % MREP)) * 1792, 7168, bar + (B_MF + slot) * 8);
          n++;
          tnext += MDELTA;
        }
        { int it3 = 0; while (var[1] != (uint32_t)s && ++it3 < SPIN_LIMIT) {} }
        const uint32_t ns = var[2];
        const uint32_t waited = n - n0 > 4 ? n - n0 - 4 : 0;
        for (uint32_t a = n0 + waited; a < ns; a++) empar ^= 1u << (a & 3);
        for (uint32_t a = ns + 1; a < n; a++) mbar_wait(bar + (B_MF + (a & 3)) * 8, (a >> 2) & 1);
        DBGV(15, n - n0);
      }
    }
    __syncwarp();
  }
  named_bar(0, CHAIN_THREADS);
  KT_END(0);
  if (CL) cluster_sync_all();
}
struct SsmArgs {
  const bf16 *lam_re, *lam_im, *log_dt, *dskip, *x, *gate_w;
  float* hloc;
  float2* hend;
  float* omg;
  float* gate;
  float4* tab;
  float* out;
};

__device__ __forceinline__ float bf2f(bf16 v) { return __bfloat162float(v); }
__device__ __forceinline__ float rbf(float v) { return __bfloat162float(__float2bfloat16_rn(v)); }
__device__ __forceinline__ float2 cmul(float2 a, float2 b) { return make_float2(a.x * b.x - a.y * b.y, a.x * b.y + a.y * b.x); }
__device__ __forceinline__ float2 ssm_z(const SsmArgs& a, int ch) {
  const float dt = rbf(expf(bf2f(a.log_dt[ch])));
  return make_float2(dt * bf2f(a.lam_re[ch]), dt * bf2f(a.lam_im[ch]));
}
__device__ __forceinline__ float2 cexp_n(float2 z, float n) {
  float sn, cs;
  sincosf(z.y * n, &sn, &cs);
  const float e = expf(z.x * n);
  return make_float2(e * cs, e * sn);
}

__global__ void __launch_bounds__(128) gate_kernel(SsmArgs args) {
  const int warp = threadIdx.x >> 5, lane = threadIdx.x & 31;
  const int t0 = blockIdx.x * 32 + warp * 8;
  float acc[8];
#pragma unroll
  for (int tt = 0; tt < 8; tt++) acc[tt] = 0.f;
#pragma unroll
  for (int d = 2 * lane; d < DM; d += 64) {
    const __nv_bfloat162 wv = *reinterpret_cast<const __nv_bfloat162*>(args.gate_w + d);
#pragma unroll
    for (int tt = 0; tt < 8; tt++) {
      const __nv_bfloat162 xv = *reinterpret_cast<const __nv_bfloat162*>(args.x + (size_t)(t0 + tt) * DM + d);
      acc[tt] += rbf(bf2f(xv.x) * bf2f(wv.x)) + rbf(bf2f(xv.y) * bf2f(wv.y));
    }
  }
#pragma unroll
  for (int tt = 0; tt < 8; tt++) {
#pragma unroll
    for (int o = 16; o; o >>= 1) acc[tt] += __shfl_xor_sync(~0u, acc[tt], o);
    if (lane == 0) {
      const float gv = rbf(1.f / (1.f + expf(-rbf(acc[tt]))));
      args.gate[t0 + tt] = gv;
      args.omg[t0 + tt] = rbf(1.f - gv);
    }
  }
}

constexpr int S1_STAGE = 32768, S1_NST = 3, S1_SMEM = S1_NST * S1_STAGE + 256;
__global__ void __launch_bounds__(160, 2)
ssm1_kernel(const __grid_constant__ CUtensorMap tm_bre, const __grid_constant__ CUtensorMap tm_bim, const __grid_constant__ CUtensorMap tm_xp, SsmArgs args) {
  extern __shared__ __align__(1024) uint8_t smem[];
  const uint32_t sb = smem_u32(smem), bar = sb + S1_NST * S1_STAGE;
  const int tid = threadIdx.x, warp = tid >> 5, lane = tid & 31;
  const int cg = blockIdx.x, tc = blockIdx.y;
  KT_START(1);
  if (tid == 0) {
    for (int i = 0; i < 7; i++) mbar_init(bar + i * 8, 1);
    for (int i = 0; i < 3; i++) mbar_init(bar + (8 + i) * 8, 4);
    asm volatile("fence.mbarrier_init.release.cluster;" ::: "memory");
  }
  __syncthreads();
  if (warp == 4) {
    if (lane == 0) {
      for (int kc = 0; kc < 7; kc++) {
        const int st = kc % 3;
        if (kc >= 3) mbar_wait(bar + (8 + st) * 8, ((kc / 3) - 1) & 1);
        mbar_expect_tx(bar + kc * 8, S1_STAGE);
        tma_load_2d(sb + st * S1_STAGE, &tm_bre, kc * 64, cg * 64, bar + kc * 8);
        tma_load_2d(sb + st * S1_STAGE + 8192, &tm_bim, kc * 64, cg * 64, bar + kc * 8);
        tma_load_4d(sb + st * S1_STAGE + 16384, &tm_xp, kc * 64, 0, tc * 4, 0, bar + kc * 8);
      }
    }
    return;
  }
  const int g = lane >> 2, q = lane & 3;
  float2 zz[2]; float lre[2], lim[2];
#pragma unroll
  for (int r = 0; r < 2; r++) { const int ch = cg * 64 + warp * 16 + g + r * 8; zz[r] = ssm_z(args, ch); lre[r] = bf2f(args.lam_re[ch]); lim[r] = bf2f(args.lam_im[ch]); }
  float ur[64], ui[64];
#pragma unroll 1
  for (int kc = 0; kc < 7; kc++) {
    const int st = kc % 3;
    mbar_wait(bar + kc * 8, 0);
    const uint32_t b0 = sb + st * S1_STAGE;
    wg_fence();
#pragma unroll
    for (int kk = 0; kk < 4; kk++) {
      wgmma_ss_n128(ur, desc_sw128(b0 + kk * 32), desc_sw128(b0 + 16384 + kk * 32), (kc | kk) != 0);
      wgmma_ss_n128(ui, desc_sw128(b0 + 8192 + kk * 32), desc_sw128(b0 + 16384 + kk * 32), (kc | kk) != 0);
    }
    wg_commit();
    wg_wait<0>();
    if (lane == 0) mbar_arrive(bar + (8 + st) * 8);
  }
#pragma unroll
  for (int r = 0; r < 2; r++) {
    const int ch = cg * 64 + warp * 16 + g + r * 8;
    const float2 z = zz[r];
    const float2 lam = cexp_n(z, 1.f);
    const float lr = lre[r], li = lim[r];
    const float den = lr * lr + li * li;
    const float2 num = make_float2(lam.x - 1.f, lam.y);
    const float2 coef = make_float2((num.x * lr + num.y * li) / den, (num.y * lr - num.x * li) / den);
    float2 hs = make_float2(0.f, 0.f);
#pragma unroll
    for (int i = 0; i < 32; i++) {
      const int idx = (i >> 1) * 4 + r * 2 + (i & 1);
      const float2 bu = cmul(coef, make_float2(ur[idx], ui[idx]));
      hs = make_float2(fmaf(lam.x, hs.x, fmaf(-lam.y, hs.y, bu.x)), fmaf(lam.x, hs.y, fmaf(lam.y, hs.x, bu.y)));
      ur[idx] = hs.x; ui[idx] = hs.y;
    }
    const float2 l32 = cexp_n(z, 32.f);
    if (tc == 0 && q == 0) {
      const float2 l128 = cexp_n(z, 128.f);
      args.tab[ch * 2] = make_float4(lam.x, lam.y, l32.x, l32.y);
      args.tab[ch * 2 + 1] = make_float4(l128.x, l128.y, 0.f, 0.f);
    }
    float2 carry = make_float2(0.f, 0.f);
#pragma unroll
    for (int qq = 0; qq < 3; qq++) {
      const float ex = __shfl_sync(~0u, hs.x, (lane & ~3) + qq), ey = __shfl_sync(~0u, hs.y, (lane & ~3) + qq);
      if (qq < q) { const float2 t = cmul(l32, carry); carry = make_float2(t.x + ex, t.y + ey); }
    }
    float2 p = lam;
    float4* dre = reinterpret_cast<float4*>(args.hloc) + ((((size_t)tc * 7 + cg) * 4 + warp) * 2 + r) * 256 + lane;
    float4* dim = dre + (size_t)DM * SEQ / 4;
#pragma unroll
    for (int i4 = 0; i4 < 8; i4++) {
      float vr[4], vi[4];
#pragma unroll
      for (int e = 0; e < 4; e++) {
        const int i = i4 * 4 + e, idx = (i >> 1) * 4 + r * 2 + (i & 1);
        const float2 t = cmul(p, carry);
        vr[e] = ur[idx] + t.x; vi[e] = ui[idx] + t.y;
        p = cmul(p, lam);
      }
      dre[i4 * 32] = make_float4(vr[0], vr[1], vr[2], vr[3]);
      dim[i4 * 32] = make_float4(vi[0], vi[1], vi[2], vi[3]);
      if (i4 == 7 && q == 3) args.hend[tc * DM + ch] = make_float2(vr[3], vi[3]);
    }
  }
  KT_END(1);
}

constexpr int S2_A = 896 * 128, S2_NST = 3, S2_SMEM = S2_A + S2_NST * XT_BYTES + 1024;
__global__ void __launch_bounds__(288, 1)
ssm2_kernel(const __grid_constant__ CUtensorMap tm_cre, const __grid_constant__ CUtensorMap tm_cim, SsmArgs args) {
  extern __shared__ __align__(1024) uint8_t smem[];
  const uint32_t sb = smem_u32(smem), bar = sb + S2_A + S2_NST * XT_BYTES;
  float* sg = reinterpret_cast<float*>(smem + S2_A + S2_NST * XT_BYTES + 512);
  const int tid = threadIdx.x, warp = tid >> 5, lane = tid & 31;
  const int t0 = blockIdx.x * 64, chunk = t0 >> 7, tau0 = t0 & 127;
  KT_START(2);
  if (tid == 0) {
    for (int i = 0; i < 28; i++) mbar_init(bar + i * 8, 1);
    for (int i = 0; i < 3; i++) mbar_init(bar + (28 + i) * 8, 4);
    asm volatile("fence.mbarrier_init.release.cluster;" ::: "memory");
  }
  __syncthreads();
  if (warp == 8) {
    if (lane == 0) {
      for (int i = 0; i < 28; i++) {
        const int st = i % 3, kc = i >> 1;
        if (i >= 3) mbar_wait(bar + (28 + st) * 8, ((i / 3) - 1) & 1);
        mbar_expect_tx(bar + i * 8, XT_BYTES);
        tma_load_2d(sb + S2_A + st * XT_BYTES, kc < 7 ? &tm_cre : &tm_cim, (kc % 7) * 64, (i & 1) * 224, bar + i * 8);
      }
    }
    return;
  }
  if (tid < 64) sg[tid] = args.gate[t0 + tid];
  for (int it = tid; it < DM * 2; it += 256) {
    const int qi = it & 1, gg = (it >> 1) & 7, r = (it >> 4) & 1, cw = it >> 5;
    const int ch = cw * 16 + r * 8 + gg;
    const float4 tb0 = args.tab[ch * 2], tb1 = args.tab[ch * 2 + 1];
    float2 e[15];
#pragma unroll
    for (int c = 0; c < 15; c++) e[c] = c < chunk ? args.hend[c * DM + ch] : make_float2(0.f, 0.f);
    const int qq = (tau0 >> 5) + qi;
    const float4* sre = reinterpret_cast<const float4*>(args.hloc) + (((size_t)chunk * 28 + cw) * 2 + r) * 256 + gg * 4 + qq;
    const float4* sim = sre + (size_t)DM * SEQ / 4;
    float4 vr4[8], vi4[8];
#pragma unroll
    for (int i4 = 0; i4 < 8; i4++) { vr4[i4] = sre[i4 * 32]; vi4[i4] = sim[i4 * 32]; }
    const float2 l128 = make_float2(tb1.x, tb1.y), lam = make_float2(tb0.x, tb0.y), l32 = make_float2(tb0.z, tb0.w);
    float2 hin = make_float2(0.f, 0.f);
#pragma unroll
    for (int c = 0; c < 15; c++) if (c < chunk) { const float2 t = cmul(l128, hin); hin = make_float2(t.x + e[c].x, t.y + e[c].y); }
    float2 p = cmul(lam, hin);
    for (int k = 0; k < qq; k++) p = cmul(p, l32);
#pragma unroll
    for (int m = 0; m < 4; m++) {
      float vr[8] = {vr4[2 * m].x, vr4[2 * m].y, vr4[2 * m].z, vr4[2 * m].w, vr4[2 * m + 1].x, vr4[2 * m + 1].y, vr4[2 * m + 1].z, vr4[2 * m + 1].w};
      float vi[8] = {vi4[2 * m].x, vi4[2 * m].y, vi4[2 * m].z, vi4[2 * m].w, vi4[2 * m + 1].x, vi4[2 * m + 1].y, vi4[2 * m + 1].z, vi4[2 * m + 1].w};
#pragma unroll
      for (int k = 0; k < 8; k++) { vr[k] = 2.f * (vr[k] + p.x); vi[k] = -2.f * (vi[k] + p.y); p = cmul(p, lam); }
      const uint4 pr = make_uint4(pack_bf16(vr[0], vr[1]), pack_bf16(vr[2], vr[3]), pack_bf16(vr[4], vr[5]), pack_bf16(vr[6], vr[7]));
      const uint4 pi = make_uint4(pack_bf16(vi[0], vi[1]), pack_bf16(vi[2], vi[3]), pack_bf16(vi[4], vi[5]), pack_bf16(vi[6], vi[7]));
      const int m8 = qi * 4 + m;
      *reinterpret_cast<uint4*>(smem + ch * 128 + ((m8 ^ (ch & 7)) << 4)) = pr;
      *reinterpret_cast<uint4*>(smem + (DM + ch) * 128 + ((m8 ^ (ch & 7)) << 4)) = pi;
    }
  }
  fence_async_smem();
  named_bar(1, 256);
  const int wg = warp >> 2, w = warp & 3;
  float acc[112];
#pragma unroll 1
  for (int kc = 0; kc < 14; kc++) {
    const int i = kc * 2 + wg, st = i % 3;
    mbar_wait(bar + i * 8, 0);
    const uint32_t bb = sb + S2_A + st * XT_BYTES;
    wg_fence();
#pragma unroll
    for (int kk = 0; kk < 4; kk++) {
      const uint64_t da = desc_sw128(sb + (kc * 64 + kk * 16) * 128);
      wgmma_ss_n112_ta(acc, da, desc_sw128(bb + kk * 32), (kc | kk) != 0);
      wgmma_ss_n112_ta(acc + 56, da, desc_sw128(bb + 14336 + kk * 32), (kc | kk) != 0);
    }
    wg_commit();
    wg_wait<0>();
    if (lane == 0) mbar_arrive(bar + (28 + st) * 8);
  }
  const int g = lane >> 2, q = lane & 3;
  named_bar(1, 256);
  float* stg = reinterpret_cast<float*>(smem);
#pragma unroll
  for (int r = 0; r < 2; r++)
#pragma unroll
    for (int nt = 0; nt < 28; nt++)
      *reinterpret_cast<float2*>(stg + (w * 16 + g + r * 8) * 456 + wg * 224 + nt * 8 + 2 * q) = make_float2(acc[nt * 4 + r * 2], acc[nt * 4 + r * 2 + 1]);
  named_bar(1, 256);
  for (int it = tid; it < 64 * 112; it += 256) {
    const int tl = it / 112, d = (it % 112) * 4;
    const float4 y = *reinterpret_cast<const float4*>(stg + tl * 456 + d);
    const uint2 xu = *reinterpret_cast<const uint2*>(args.x + (size_t)(t0 + tl) * DM + d), du = *reinterpret_cast<const uint2*>(args.dskip + d);
    const float gv = sg[tl];
    float4 o;
    o.x = gv * (y.x + rbf(__uint_as_float(xu.x << 16) * __uint_as_float(du.x << 16)));
    o.y = gv * (y.y + rbf(__uint_as_float(xu.x & 0xFFFF0000u) * __uint_as_float(du.x & 0xFFFF0000u)));
    o.z = gv * (y.z + rbf(__uint_as_float(xu.y << 16) * __uint_as_float(du.y << 16)));
    o.w = gv * (y.w + rbf(__uint_as_float(xu.y & 0xFFFF0000u) * __uint_as_float(du.y & 0xFFFF0000u)));
    red_v4(args.out + (size_t)(t0 + tl) * DM + d, o.x, o.y, o.z, o.w);
  }
  KT_END(2);
}
struct AttnArgs {
  uint32_t* flag;
  uint32_t* ticket;
  const float* omg;
  float* out;
  uint32_t total_ctas;
};
#define AT_SPLIT_V 56
constexpr int AT_SPLIT = AT_SPLIT_V;
constexpr int AT_ITEMS = AT_SPLIT * 2 + (NSEG - AT_SPLIT) * 8;
constexpr int AT_X = 2 * 7 * 4096;
constexpr int AT_T = 7 * 5120;
constexpr int AT_OFF_K = AT_X, AT_OFF_Y = AT_X + 2 * AT_T;
constexpr int AT_OFF_P = AT_X + 4 * AT_T;
constexpr int AT_OFF_BAR = AT_OFF_P + 2 * 2 * 3072;
constexpr int AT_STG = 32 * 68 * 4;
constexpr int AT_OFF_STG = AT_OFF_BAR + 256;
constexpr int AT_SMEM = AT_OFF_STG + 2 * AT_STG;
constexpr uint32_t FLAG_TARGET = 112;

__device__ __forceinline__ void attn_decode(int item, int& s, int& p0, int& np) {
  if (item < AT_SPLIT * 2) { s = item >> 1; p0 = (item & 1) * 4; np = 4; }
  else { const int i = item - AT_SPLIT * 2; s = AT_SPLIT + (i >> 3); p0 = i & 7; np = 1; }
}

#define ATS(i) do {} while (0)
__device__ __forceinline__ void attn_consumer(uint8_t* smem, uint32_t sb, const AttnArgs& args, int wg, int w, int lane) {
  const uint32_t bar = sb + AT_OFF_BAR;
  volatile int* s_item = reinterpret_cast<volatile int*>(smem + AT_OFF_BAR + 128);
  float* stg = reinterpret_cast<float*>(smem + AT_OFF_STG + wg * AT_STG);
  const int g = lane >> 2, q = lane & 3;
  const int C0 = wg * 4;
  int m = 0;
  long long tprev = clock64(); (void)tprev;
  for (int n = 0;; n++) {
    mbar_wait(bar + (0 + (n & 1)) * 8, (n >> 1) & 1);
    ATS(0);
    const int item = s_item[n & 1];
    if (item >= AT_ITEMS) break;
    int s, p0, np;
    attn_decode(item, s, p0, np);
    const uint64_t dx = desc_sw128(sb + (n & 1) * (7 * 4096));
    float acc[4][16];
    float om4[4];
#pragma unroll
    for (int i = 0; i < 4; i++) om4[i] = args.omg[s * SEG + i * 8 + ((w * 32 + lane) >> 4)];
#pragma unroll 1
    for (int pp = 0; pp < np; pp++, m++) {
      const uint64_t dk = desc_sw128(sb + AT_OFF_K + wg * AT_T);
      mbar_wait(bar + 4 * 8, m & 1);
      ATS(1);
      float sc[20];
      wg_fence();
#pragma unroll
      for (int kc = 0; kc < 7; kc++)
#pragma unroll
        for (int kk = 0; kk < 4; kk++) wgmma_ss_n40(sc, dx + (uint64_t)(kc * 256 + kk * 2), dk + (uint64_t)(kc * 320 + kk * 2), (kc | kk) != 0);
      wg_commit();
      wg_wait<0>();
      __syncwarp();
      if (lane == 0) { mbar_arrive(bar + 5 * 8); if (pp == np - 1) mbar_arrive(bar + (2 + (n & 1)) * 8); }
      ATS(2);
      const uint32_t pbuf = sb + AT_OFF_P + (m & 1) * (2 * 3072);
      if (w < 2) {
#pragma unroll
        for (int r = 0; r < 2; r++) {
          const int t = w * 16 + g + r * 8;
          float v[10];
          float mx = -3.0e38f;
#pragma unroll
          for (int nt = 0; nt < 5; nt++)
#pragma unroll
            for (int e = 0; e < 2; e++) {
              const int key = nt * 8 + 2 * q + e;
              const float x = (key - NMEM <= t) ? sc[nt * 4 + r * 2 + e] : -1.0e9f;
              v[nt * 2 + e] = x; mx = fmaxf(mx, x);
            }
          mx = fmaxf(mx, __shfl_xor_sync(~0u, mx, 1));
          mx = fmaxf(mx, __shfl_xor_sync(~0u, mx, 2));
          float l = 0.f;
#pragma unroll
          for (int k = 0; k < 10; k++) { v[k] = ex2((v[k] - mx) * L2E); l += v[k]; }
          l += __shfl_xor_sync(~0u, l, 1);
          l += __shfl_xor_sync(~0u, l, 2);
          const float rl = __fdividef(1.f, l);
          const uint32_t dst = pbuf + wg * 3072 + (2 * w + r) * 768 + g * 16 + q * 4;
#pragma unroll
          for (int nt = 0; nt < 5; nt++) asm volatile("st.shared.u32 [%0], %1;" ::"r"(dst + nt * 128), "r"(pack_bf16(v[2 * nt] * rl, v[2 * nt + 1] * rl)) : "memory");
        }
        fence_async_smem();
      }
      ATS(3);
      named_bar(1, 256);
      ATS(4);
      const uint64_t dp = ((uint64_t)((pbuf & 0x3FFFF) >> 4)) | ((uint64_t)(128 >> 4) << 16) | ((uint64_t)(768 >> 4) << 32);
      const uint64_t dy = desc_sw128(sb + AT_OFF_Y);
      mbar_wait(bar + 6 * 8, m & 1);
      ATS(5);
      wg_fence();
#pragma unroll
      for (int c = 0; c < 4; c++) {
        const int cc = min(C0 + c, 6);
#pragma unroll
        for (int hk = 0; hk < 6; hk++) {
          const int hd = hk / 3, kk = hk % 3;
          wgmma_ss_n32_ta(acc[c], dy + (uint64_t)(hd * (AT_T >> 4) + cc * 320 + kk * 128), dp + (uint64_t)(hd * 192 + kk * 16), (pp | hk) != 0);
        }
      }
      wg_commit();
      wg_wait<0>();
      __syncwarp();
      if (lane == 0) mbar_arrive(bar + 7 * 8);
      ATS(6);
    }
    {
      const int tid7 = w * 32 + lane;
#pragma unroll
      for (int c = 0; c < 4; c++) {
        if (C0 + c < 7) {
#pragma unroll
          for (int nt = 0; nt < 4; nt++) {
            stg[(8 * nt + 2 * q) * 68 + 16 * w + g] = acc[c][4 * nt];
            stg[(8 * nt + 2 * q + 1) * 68 + 16 * w + g] = acc[c][4 * nt + 1];
            stg[(8 * nt + 2 * q) * 68 + 16 * w + g + 8] = acc[c][4 * nt + 2];
            stg[(8 * nt + 2 * q + 1) * 68 + 16 * w + g + 8] = acc[c][4 * nt + 3];
          }
          named_bar(2 + wg, 128);
#pragma unroll
          for (int i = 0; i < 4; i++) {
            const int row = i * 8 + (tid7 >> 4), col = (tid7 & 15) * 4;
            const float4 v = *reinterpret_cast<const float4*>(stg + row * 68 + col);
            const float om = om4[i];
            red_v4(args.out + (size_t)(s * SEG + row) * DM + (C0 + c) * 64 + col, om * v.x, om * v.y, om * v.z, om * v.w);
          }
          named_bar(2 + wg, 128);
        }
      }
    }
    ATS(7);
  }
}

__global__ void __launch_bounds__(384, 1)
attn_kernel(const __grid_constant__ CUtensorMap tm_x, const __grid_constant__ CUtensorMap tm_k, const __grid_constant__ CUtensorMap tm_y, AttnArgs args) {
  extern __shared__ __align__(1024) uint8_t smem[];
  const uint32_t sb = smem_u32(smem), bar = sb + AT_OFF_BAR;
  volatile int* s_item = reinterpret_cast<volatile int*>(smem + AT_OFF_BAR + 128);
  const int tid = threadIdx.x, warp = tid >> 5, lane = tid & 31;
  KT_START(3);
  if (tid == 0) {
    mbar_init(bar + 0 * 8, 1); mbar_init(bar + 1 * 8, 1); mbar_init(bar + 2 * 8, 8); mbar_init(bar + 3 * 8, 8);
    mbar_init(bar + 4 * 8, 1); mbar_init(bar + 5 * 8, 8); mbar_init(bar + 6 * 8, 1); mbar_init(bar + 7 * 8, 8);
    asm volatile("fence.mbarrier_init.release.cluster;" ::: "memory");
  }
  for (int i = tid; i < AT_OFF_BAR / 16; i += 384) *reinterpret_cast<uint4*>(smem + i * 16) = make_uint4(0, 0, 0, 0);
  fence_async_smem();
  __syncthreads();
  const int wg = __shfl_sync(0xffffffffu, warp >> 2, 0);
  if (wg == 2) {
    asm volatile("setmaxnreg.dec.sync.aligned.u32 40;");
    if (tid == 256) {
      int m = 0;
      for (int n = 0;; n++) {
        const int sl = n & 1;
        if (n >= 2) mbar_wait(bar + (2 + sl) * 8, ((n >> 1) - 1) & 1);
        const int item = (int)atomicAdd(args.ticket, 1u);
        s_item[sl] = item;
        if (item >= AT_ITEMS) {
          mbar_arrive(bar + sl * 8);
          if (atomicAdd(args.ticket + 1, 1u) == args.total_ctas - 1) {
            for (int i = 0; i < NSEG; i++) args.flag[i] = 0u;
            args.ticket[0] = 0u; args.ticket[1] = 0u;
          }
          break;
        }
        int s, p0, np;
        attn_decode(item, s, p0, np);
        mbar_expect_tx(bar + sl * 8, 7 * 4096);
        tma_load_3d(sb + sl * (7 * 4096), &tm_x, 0, s * SEG, 0, bar + sl * 8);
        { int it = 0; while (ld_acquire(args.flag + s) < FLAG_TARGET && ++it < SPIN_LIMIT) __nanosleep(100); }
        fence_async_all();
        for (int pp = 0; pp < np; pp++, m++) {
          const int row = (((p0 + pp) * 2) * NSEG + s) * LKEY;
          if (m >= 1) mbar_wait(bar + 5 * 8, (m - 1) & 1);
          mbar_expect_tx(bar + 4 * 8, 2 * AT_T);
          tma_load_3d(sb + AT_OFF_K, &tm_k, 0, row, 0, bar + 4 * 8);
          tma_load_3d(sb + AT_OFF_K + AT_T, &tm_k, 0, row + NSEG * LKEY, 0, bar + 4 * 8);
          if (m >= 1) mbar_wait(bar + 7 * 8, (m - 1) & 1);
          mbar_expect_tx(bar + 6 * 8, 2 * AT_T);
          tma_load_3d(sb + AT_OFF_Y, &tm_y, 0, row, 0, bar + 6 * 8);
          tma_load_3d(sb + AT_OFF_Y + AT_T, &tm_y, 0, row + NSEG * LKEY, 0, bar + 6 * 8);
        }
      }
    }
  } else {
    asm volatile("setmaxnreg.inc.sync.aligned.u32 232;");
    attn_consumer(smem, sb, args, wg, warp & 3, lane);
    KT_END(3);
  }
}
__device__ bf16 g_Kall[(size_t)NH * NSEG * LKEY * DM];
__device__ bf16 g_Yall[(size_t)NH * NSEG * LKEY * DM];
__device__ uint32_t g_M[65 * 1792 * 16];
__device__ float4 g_S[(size_t)NSEG * NH * 5 * 32 + (size_t)NSEG * NJ * 16 * 16 * 8];
__device__ uint32_t g_flag[NSEG + 64];
__device__ float g_hloc[2 * DM * SEQ];
__device__ float2 g_hend[16 * DM];
__device__ float g_omg[2 * SEQ];
__device__ float4 g_tab[2 * DM];
__device__ uint32_t g_dbg[112 * 1024 + 112 * 4 + 112 * 8];

typedef CUresult (*EncodeFn)(CUtensorMap*, CUtensorMapDataType, cuuint32_t, void*, const cuuint64_t*, const cuuint64_t*, const cuuint32_t*,
                             const cuuint32_t*, CUtensorMapInterleave, CUtensorMapSwizzle, CUtensorMapL2promotion, CUtensorMapFloatOOBfill);

static bool make_map_2d(EncodeFn enc, CUtensorMap* m, const void* ptr, uint64_t cols, uint64_t rows, uint32_t box_cols, uint32_t box_rows) {
  cuuint64_t dims[2] = {cols, rows};
  cuuint64_t strides[1] = {cols * 2};
  cuuint32_t box[2] = {box_cols, box_rows};
  cuuint32_t es[2] = {1, 1};
  return enc(m, CU_TENSOR_MAP_DATA_TYPE_BFLOAT16, 2, const_cast<void*>(ptr), dims, strides, box, es, CU_TENSOR_MAP_INTERLEAVE_NONE,
             CU_TENSOR_MAP_SWIZZLE_128B, CU_TENSOR_MAP_L2_PROMOTION_L2_256B, CU_TENSOR_MAP_FLOAT_OOB_FILL_NONE) == CUDA_SUCCESS;
}
static bool make_map_rows(EncodeFn enc, CUtensorMap* m, const void* ptr, uint64_t rows, uint32_t box_rows) {
  cuuint64_t dims[3] = {64, rows, 7};
  cuuint64_t strides[2] = {(cuuint64_t)DM * 2, 128};
  cuuint32_t box[3] = {64, box_rows, 7};
  cuuint32_t es[3] = {1, 1, 1};
  return enc(m, CU_TENSOR_MAP_DATA_TYPE_BFLOAT16, 3, const_cast<void*>(ptr), dims, strides, box, es, CU_TENSOR_MAP_INTERLEAVE_NONE,
             CU_TENSOR_MAP_SWIZZLE_128B, CU_TENSOR_MAP_L2_PROMOTION_L2_256B, CU_TENSOR_MAP_FLOAT_OOB_FILL_NONE) == CUDA_SUCCESS;
}
static bool make_map_xperm(EncodeFn enc, CUtensorMap* m, const void* ptr) {
  cuuint64_t dims[4] = {(cuuint64_t)DM, 2, 64, 16};
  cuuint64_t strides[3] = {(cuuint64_t)DM * 2, (cuuint64_t)DM * 2 * 32, (cuuint64_t)DM * 2 * 2};
  cuuint32_t box[4] = {64, 2, 4, 16};
  cuuint32_t es[4] = {1, 1, 1, 1};
  return enc(m, CU_TENSOR_MAP_DATA_TYPE_BFLOAT16, 4, const_cast<void*>(ptr), dims, strides, box, es, CU_TENSOR_MAP_INTERLEAVE_NONE,
             CU_TENSOR_MAP_SWIZZLE_128B, CU_TENSOR_MAP_L2_PROMOTION_L2_256B, CU_TENSOR_MAP_FLOAT_OOB_FILL_NONE) == CUDA_SUCCESS;
}

#define N_ATTN 8
struct HostState {
  bool init, ok, use_cluster;
  CUtensorMap tx, tq, tk, tv, to, tka, tya, tbre, tbim, txp, tcre, tcim, tx3, tk3, ty3;
  void *pK, *pY, *pM, *pS, *pF, *pD, *pH, *pE, *pO, *pT;
  cudaStream_t side, side2;
  cudaEvent_t ev_start, ev_join, ev_gate, ev_join2;
  int n_free, n_attn;
  const void* key[17];
  void* key_out;
};
static HostState g_hs;

}

extern "C" void kernel_launch(void* const* d_in, const int* in_sizes, int n_in, void* d_out, int out_size) {
  HostState& S = g_hs;
  (void)in_sizes; (void)n_in; (void)out_size;
  cudaStream_t st = cudaStreamPerThread;
  bool same = S.init;
  for (int i = 0; i < 17 && same; i++) same = S.key[i] == d_in[i];
  if (!same) {
    EncodeFn enc = nullptr;
    cudaDriverEntryPointQueryResult qr;
    cudaGetDriverEntryPoint("cuTensorMapEncodeTiled", (void**)&enc, cudaEnableDefault, &qr);
    cudaGetSymbolAddress(&S.pK, g_Kall); cudaGetSymbolAddress(&S.pY, g_Yall); cudaGetSymbolAddress(&S.pM, g_M); cudaGetSymbolAddress(&S.pS, g_S);
    cudaGetSymbolAddress(&S.pF, g_flag); cudaGetSymbolAddress(&S.pD, g_dbg); cudaGetSymbolAddress(&S.pH, g_hloc); cudaGetSymbolAddress(&S.pE, g_hend);
    cudaGetSymbolAddress(&S.pO, g_omg); cudaGetSymbolAddress(&S.pT, g_tab);
    S.ok = enc && make_map_2d(enc, &S.tx, d_in[0], DM, SEQ, 64, 32) && make_map_2d(enc, &S.tq, d_in[11], 4096, DM, 64, 64) &&
           make_map_2d(enc, &S.tk, d_in[12], 4096, DM, 64, 224) && make_map_2d(enc, &S.tv, d_in[13], 4096, DM, 64, 224) &&
           make_map_2d(enc, &S.to, d_in[14], DM, 4096, 64, 256) && make_map_2d(enc, &S.tka, S.pK, DM, NH * NSEG * LKEY, 64, LKEY) &&
           make_map_2d(enc, &S.tya, S.pY, DM, NH * NSEG * LKEY, 64, LKEY) && make_map_2d(enc, &S.tbre, d_in[3], DM, DM, 64, 64) &&
           make_map_2d(enc, &S.tbim, d_in[4], DM, DM, 64, 64) && make_map_xperm(enc, &S.txp, d_in[0]) &&
           make_map_2d(enc, &S.tcre, d_in[5], DM, DM, 64, 224) && make_map_2d(enc, &S.tcim, d_in[6], DM, DM, 64, 224) &&
           make_map_rows(enc, &S.tx3, d_in[0], SEQ, SEG) && make_map_rows(enc, &S.tk3, S.pK, NH * NSEG * LKEY, LKEY) && make_map_rows(enc, &S.ty3, S.pY, NH * NSEG * LKEY, LKEY);
    if (!S.init) {
      cudaFuncSetAttribute(chain_kernel<true>, cudaFuncAttributeMaxDynamicSharedMemorySize, SMEM_CHAIN);
      cudaFuncSetAttribute(chain_kernel<true>, cudaFuncAttributeNonPortableClusterSizeAllowed, 1);
      cudaFuncSetAttribute(chain_kernel<false>, cudaFuncAttributeMaxDynamicSharedMemorySize, SMEM_CHAIN);
      cudaFuncSetAttribute(ssm1_kernel, cudaFuncAttributeMaxDynamicSharedMemorySize, S1_SMEM);
      cudaFuncSetAttribute(ssm2_kernel, cudaFuncAttributeMaxDynamicSharedMemorySize, S2_SMEM);
      cudaFuncSetAttribute(attn_kernel, cudaFuncAttributeMaxDynamicSharedMemorySize, AT_SMEM);
      cudaLaunchConfig_t cfg = {};
      cfg.gridDim = dim3(112); cfg.blockDim = dim3(CHAIN_THREADS); cfg.dynamicSmemBytes = SMEM_CHAIN;
      cudaLaunchAttribute at[1];
      at[0].id = cudaLaunchAttributeClusterDimension; at[0].val.clusterDim.x = 16; at[0].val.clusterDim.y = 1; at[0].val.clusterDim.z = 1;
      cfg.attrs = at; cfg.numAttrs = 1;
      int nc = 0;
      if (cudaOccupancyMaxActiveClusters(&nc, chain_kernel<true>, &cfg) != cudaSuccess) { nc = 0; (void)cudaGetLastError(); }
      S.use_cluster = nc >= 7;
      int sms = 132;
      cudaDeviceGetAttribute(&sms, cudaDevAttrMultiProcessorCount, 0);
      S.n_free = sms - 112 > 1 ? sms - 112 : 1;
      S.n_attn = S.n_free >= 16 ? N_ATTN : (S.n_free + 1) / 2;
      cudaStreamCreateWithFlags(&S.side, cudaStreamNonBlocking);
      cudaEventCreateWithFlags(&S.ev_start, cudaEventDisableTiming);
      cudaEventCreateWithFlags(&S.ev_join, cudaEventDisableTiming);
      cudaStreamCreateWithFlags(&S.side2, cudaStreamNonBlocking);
      cudaEventCreateWithFlags(&S.ev_gate, cudaEventDisableTiming);
      cudaEventCreateWithFlags(&S.ev_join2, cudaEventDisableTiming);
    }
    for (int i = 0; i < 17; i++) S.key[i] = d_in[i];
    S.init = true;
  }
  if (!S.ok) return;

  ChainArgs ca;
  ca.mem0 = (const bf16*)d_in[10]; ca.Mg = (uint32_t*)S.pM; ca.Sg = (float4*)S.pS; ca.flag = (uint32_t*)S.pF; ca.dbg = (uint32_t*)S.pD;
  {
    cudaLaunchConfig_t cfg = {};
    cfg.gridDim = dim3(112); cfg.blockDim = dim3(CHAIN_THREADS); cfg.dynamicSmemBytes = SMEM_CHAIN; cfg.stream = st;
    cudaLaunchAttribute at[2];
    at[0].id = cudaLaunchAttributeLaunchCompletionEvent; at[0].val.launchCompletionEvent.event = S.ev_start; at[0].val.launchCompletionEvent.flags = 0;
    at[1].id = cudaLaunchAttributeClusterDimension; at[1].val.clusterDim.x = 16; at[1].val.clusterDim.y = 1; at[1].val.clusterDim.z = 1;
    cfg.attrs = at; cfg.numAttrs = S.use_cluster ? 2 : 1;
    if (S.use_cluster) cudaLaunchKernelEx(&cfg, chain_kernel<true>, S.tx, S.tq, S.tk, S.tv, S.to, S.tka, S.tya, S.tx3, ca);
    else cudaLaunchKernelEx(&cfg, chain_kernel<false>, S.tx, S.tq, S.tk, S.tv, S.to, S.tka, S.tya, S.tx3, ca);
  }
  SsmArgs sa;
  sa.lam_re = (const bf16*)d_in[1]; sa.lam_im = (const bf16*)d_in[2]; sa.log_dt = (const bf16*)d_in[7]; sa.dskip = (const bf16*)d_in[8];
  sa.x = (const bf16*)d_in[0]; sa.gate_w = (const bf16*)d_in[16];
  sa.hloc = (float*)S.pH; sa.hend = (float2*)S.pE; sa.omg = (float*)S.pO; sa.gate = (float*)S.pO + SEQ; sa.tab = (float4*)S.pT; sa.out = (float*)d_out;
  AttnArgs aa;
  aa.flag = (uint32_t*)S.pF; aa.ticket = (uint32_t*)S.pF + NSEG; aa.omg = (const float*)S.pO; aa.out = (float*)d_out;
  const int n_attn2 = S.n_free - S.n_attn > 0 ? S.n_free - S.n_attn : 0;
  aa.total_ctas = (uint32_t)(S.n_attn + n_attn2);
  cudaStreamWaitEvent(S.side, S.ev_start, 0);
  cudaMemsetAsync(d_out, 0, sizeof(float) * SEQ * DM, S.side);
  gate_kernel<<<64, 128, 0, S.side>>>(sa);
  cudaEventRecord(S.ev_gate, S.side);
  attn_kernel<<<S.n_attn, 384, AT_SMEM, S.side>>>(S.tx3, S.tk3, S.ty3, aa);
  cudaStreamWaitEvent(S.side2, S.ev_gate, 0);
  ssm1_kernel<<<dim3(7, 16), 160, S1_SMEM, S.side2>>>(S.tbre, S.tbim, S.txp, sa);
  ssm2_kernel<<<32, 288, S2_SMEM, S.side2>>>(S.tcre, S.tcim, sa);
  if (n_attn2 > 0) attn_kernel<<<n_attn2, 384, AT_SMEM, S.side2>>>(S.tx3, S.tk3, S.ty3, aa);
  cudaEventRecord(S.ev_join, S.side);
  cudaEventRecord(S.ev_join2, S.side2);
  cudaStreamWaitEvent(st, S.ev_join, 0);
  cudaStreamWaitEvent(st, S.ev_join2, 0);
}
```

```cpp
#include <cuda_runtime.h>
#include <cuda_bf16.h>
#include <cuda.h>
#include <stdint.h>

typedef __nv_bfloat16 bf16;

namespace {

constexpr int NH = 16, DM = 448, DH = 256, SEQ = 2048, SEG = 32, NSEG = 64, NJ = 7, NMEM = 8, LKEY = 40;
constexpr int SPIN_LIMIT = 1 << 22;

#define KT_START(k) do {} while (0)
#define KT_END(k) do {} while (0)

__device__ __forceinline__ uint32_t smem_u32(const void* p) { return (uint32_t)__cvta_generic_to_shared(p); }
__device__ __forceinline__ void mbar_init(uint32_t a, uint32_t c) { asm volatile("mbarrier.init.shared.b64 [%0], %1;" ::"r"(a), "r"(c)); }
__device__ __forceinline__ void mbar_arrive(uint32_t a) { asm volatile("mbarrier.arrive.shared.b64 _, [%0];" ::"r"(a) : "memory"); }
__device__ __forceinline__ void mbar_expect_tx(uint32_t a, uint32_t b) { asm volatile("mbarrier.arrive.expect_tx.shared.b64 _, [%0], %1;" ::"r"(a), "r"(b) : "memory"); }
__device__ __forceinline__ bool mbar_try(uint32_t a, uint32_t parity) {
  uint32_t r;
  asm volatile("{\n.reg .pred p;\nmbarrier.try_wait.parity.shared.b64 p, [%1], %2;\nselp.u32 %0, 1, 0, p;\n}\n" : "=r"(r) : "r"(a), "r"(parity) : "memory");
  return r;
}
__device__ __forceinline__ bool mbar_try_cluster(uint32_t a, uint32_t parity) {
  uint32_t r;
  asm volatile("{\n.reg .pred p;\nmbarrier.try_wait.parity.acquire.cluster.shared.b64 p, [%1], %2;\nselp.u32 %0, 1, 0, p;\n}\n" : "=r"(r) : "r"(a), "r"(parity) : "memory");
  return r;
}
__device__ __forceinline__ bool mbar_test(uint32_t a, uint32_t parity) {
  uint32_t r;
  asm volatile("{\n.reg .pred p;\nmbarrier.test_wait.parity.shared.b64 p, [%1], %2;\nselp.u32 %0, 1, 0, p;\n}\n" : "=r"(r) : "r"(a), "r"(parity) : "memory");
  return r;
}
__device__ __forceinline__ void mbar_wait(uint32_t a, uint32_t parity) {
  int it = 0;
  while (!mbar_try(a, parity)) { if (++it > SPIN_LIMIT) break; }
}
__device__ __forceinline__ void mbar_wait_cluster(uint32_t a, uint32_t parity) {
  int it = 0;
  while (!mbar_try_cluster(a, parity)) { if (++it > SPIN_LIMIT) break; }
}
__device__ __forceinline__ uint32_t mapa(uint32_t a, uint32_t r) { uint32_t d; asm volatile("mapa.shared::cluster.u32 %0, %1, %2;" : "=r"(d) : "r"(a), "r"(r)); return d; }
__device__ __forceinline__ void cluster_sync_all() { asm volatile("barrier.cluster.arrive.aligned;\nbarrier.cluster.wait.aligned;" ::: "memory"); }
__device__ __forceinline__ void named_bar(int id, int n) { asm volatile("bar.sync %0, %1;" ::"r"(id), "r"(n) : "memory"); }
__device__ __forceinline__ void fence_async_smem() { asm volatile("fence.proxy.async.shared::cta;" ::: "memory"); }
__device__ __forceinline__ void fence_async_all() { asm volatile("fence.proxy.async;" ::: "memory"); }

__device__ __forceinline__ uint4 ld_vol_v4(const void* p) {
  uint4 v;
  asm volatile("ld.volatile.global.v4.u32 {%0,%1,%2,%3}, [%4];" : "=r"(v.x), "=r"(v.y), "=r"(v.z), "=r"(v.w) : "l"(p) : "memory");
  return v;
}
__device__ __forceinline__ uint32_t ld_acquire(const void* p) { uint32_t v; asm volatile("ld.acquire.gpu.global.u32 %0, [%1];" : "=r"(v) : "l"(p) : "memory"); return v; }
__device__ __forceinline__ void st_relaxed(void* p, uint32_t v) { asm volatile("st.relaxed.gpu.global.u32 [%0], %1;" ::"l"(p), "r"(v) : "memory"); }
__device__ __forceinline__ void red_v4(void* p, float a, float b, float c, float d) {
  asm volatile("red.relaxed.gpu.global.add.v4.f32 [%0], {%1,%2,%3,%4};" ::"l"(p), "f"(a), "f"(b), "f"(c), "f"(d) : "memory");
}
__device__ __forceinline__ void red_u32(void* p, uint32_t v) { asm volatile("red.relaxed.gpu.global.add.u32 [%0], %1;" ::"l"(p), "r"(v) : "memory"); }
__device__ __forceinline__ void st_async_v4(uint32_t addr, float a, float b, float c, float d, uint32_t mbar) {
  asm volatile("st.async.shared::cluster.mbarrier::complete_tx::bytes.v4.f32 [%0], {%1,%2,%3,%4}, [%5];" ::"r"(addr), "f"(a), "f"(b), "f"(c), "f"(d), "r"(mbar) : "memory");
}

__device__ __forceinline__ void tma_load_2d(uint32_t dst, const CUtensorMap* tm, int c0, int c1, uint32_t mbar) {
  asm volatile("cp.async.bulk.tensor.2d.shared::cluster.global.mbarrier::complete_tx::bytes [%0], [%1, {%3, %4}], [%2];" ::"r"(dst), "l"(tm), "r"(mbar), "r"(c0), "r"(c1) : "memory");
}
__device__ __forceinline__ void tma_load_2d_mc(uint32_t dst, const CUtensorMap* tm, int c0, int c1, uint32_t mbar, uint16_t mask) {
  asm volatile("cp.async.bulk.tensor.2d.shared::cluster.global.mbarrier::complete_tx::bytes.multicast::cluster [%0], [%1, {%3, %4}], [%2], %5;" ::"r"(dst), "l"(tm), "r"(mbar), "r"(c0), "r"(c1), "h"(mask) : "memory");
}
__device__ __forceinline__ void tma_load_3d(uint32_t dst, const CUtensorMap* tm, int c0, int c1, int c2, uint32_t mbar) {
  asm volatile("cp.async.bulk.tensor.3d.shared::cluster.global.mbarrier::complete_tx::bytes [%0], [%1, {%3, %4, %5}], [%2];" ::"r"(dst), "l"(tm), "r"(mbar), "r"(c0), "r"(c1), "r"(c2) : "memory");
}
__device__ __forceinline__ void tma_load_4d(uint32_t dst, const CUtensorMap* tm, int c0, int c1, int c2, int c3, uint32_t mbar) {
  asm volatile("cp.async.bulk.tensor.4d.shared::cluster.global.mbarrier::complete_tx::bytes [%0], [%1, {%3, %4, %5, %6}], [%2];" ::"r"(dst), "l"(tm), "r"(mbar), "r"(c0), "r"(c1), "r"(c2), "r"(c3) : "memory");
}
__device__ __forceinline__ void tma_store_2d(const CUtensorMap* tm, int c0, int c1, uint32_t src) {
  asm volatile("cp.async.bulk.tensor.2d.global.shared::cta.bulk_group [%0, {%2, %3}], [%1];" ::"l"(tm), "r"(src), "r"(c0), "r"(c1) : "memory");
}
__device__ __forceinline__ void bulk_load(uint32_t dst, const void* src, uint32_t bytes, uint32_t mbar) {
  asm volatile("cp.async.bulk.shared::cluster.global.mbarrier::complete_tx::bytes [%0], [%1], %2, [%3];" ::"r"(dst), "l"(src), "r"(bytes), "r"(mbar) : "memory");
}
__device__ __forceinline__ void bulk_commit() { asm volatile("cp.async.bulk.commit_group;" ::: "memory"); }
template <int N> __device__ __forceinline__ void bulk_wait_read() { asm volatile("cp.async.bulk.wait_group.read %0;" ::"n"(N) : "memory"); }
template <int N> __device__ __forceinline__ void bulk_wait() { asm volatile("cp.async.bulk.wait_group %0;" ::"n"(N) : "memory"); }

__device__ __forceinline__ void wg_fence() { asm volatile("wgmma.fence.sync.aligned;" ::: "memory"); }
__device__ __forceinline__ void wg_commit() { asm volatile("wgmma.commit_group.sync.aligned;" ::: "memory"); }
template <int N> __device__ __forceinline__ void wg_wait() { asm volatile("wgmma.wait_group.sync.aligned %0;" ::"n"(N) : "memory"); }

__device__ __forceinline__ uint64_t desc_sw128(uint32_t addr) {
  return ((uint64_t)((addr & 0x3FFFF) >> 4)) | ((uint64_t)1 << 16) | ((uint64_t)(1024 >> 4) << 32) | ((uint64_t)1 << 62);
}

__device__ __forceinline__ uint32_t pack_bf16(float lo, float hi) {
  uint32_t r;
  asm("cvt.rn.bf16x2.f32 %0, %1, %2;" : "=r"(r) : "f"(hi), "f"(lo));
  return r;
}
__device__ __forceinline__ void mma16816(float* d, uint32_t a0, uint32_t a1, uint32_t a2, uint32_t a3, uint32_t b0, uint32_t b1) {
  asm volatile("mma.sync.aligned.m16n8k16.row.col.f32.bf16.bf16.f32 {%0,%1,%2,%3}, {%4,%5,%6,%7}, {%8,%9}, {%0,%1,%2,%3};"
               : "+f"(d[0]), "+f"(d[1]), "+f"(d[2]), "+f"(d[3]) : "r"(a0), "r"(a1), "r"(a2), "r"(a3), "r"(b0), "r"(b1));
}
__device__ __forceinline__ void mma1688(float* d, uint32_t a0, uint32_t a1, uint32_t b0) {
  asm volatile("mma.sync.aligned.m16n8k8.row.col.f32.bf16.bf16.f32 {%0,%1,%2,%3}, {%4,%5}, {%6}, {%0,%1,%2,%3};"
               : "+f"(d[0]), "+f"(d[1]), "+f"(d[2]), "+f"(d[3]) : "r"(a0), "r"(a1), "r"(b0));
}
__device__ __forceinline__ void ldsm_x4(uint32_t* r, uint32_t addr) {
  asm volatile("ldmatrix.sync.aligned.m8n8.x4.shared.b16 {%0,%1,%2,%3}, [%4];" : "=r"(r[0]), "=r"(r[1]), "=r"(r[2]), "=r"(r[3]) : "r"(addr) : "memory");
}
__device__ __forceinline__ void ldsm_x4_t(uint32_t* r, uint32_t addr) {
  asm volatile("ldmatrix.sync.aligned.m8n8.x4.trans.shared.b16 {%0,%1,%2,%3}, [%4];" : "=r"(r[0]), "=r"(r[1]), "=r"(r[2]), "=r"(r[3]) : "r"(addr) : "memory");
}
__device__ __forceinline__ void ldsm_x2_t(uint32_t* r, uint32_t addr) {
  asm volatile("ldmatrix.sync.aligned.m8n8.x2.trans.shared.b16 {%0,%1}, [%2];" : "=r"(r[0]), "=r"(r[1]) : "r"(addr) : "memory");
}
__device__ __forceinline__ void stsm_x4_t(uint32_t addr, uint32_t r0, uint32_t r1, uint32_t r2, uint32_t r3) {
  asm volatile("stmatrix.sync.aligned.m8n8.x4.trans.shared.b16 [%0], {%1,%2,%3,%4};" ::"r"(addr), "r"(r0), "r"(r1), "r"(r2), "r"(r3) : "memory");
}
__device__ __forceinline__ uint32_t movm_t(uint32_t a) { uint32_t d; asm volatile("movmatrix.sync.aligned.m8n8.trans.b16 %0, %1;" : "=r"(d) : "r"(a)); return d; }
__device__ __forceinline__ float ex2(float x) { float y; asm("ex2.approx.ftz.f32 %0, %1;" : "=f"(y) : "f"(x)); return y; }

__device__ __forceinline__ void wgmma_ss_n112(float* d, uint64_t descA, uint64_t descB, int scaleD) {
  asm volatile("{\n.reg .pred p;\nsetp.ne.b32 p, %58, 0;\n"
    "wgmma.mma_async.sync.aligned.m64n112k16.f32.bf16.bf16 {%0,%1,%2,%3,%4,%5,%6,%7,%8,%9,%10,%11,%12,%13,%14,%15,%16,%17,%18,%19,%20,%21,%22,%23,%24,%25,%26,%27,%28,%29,%30,%31,%32,%33,%34,%35,%36,%37,%38,%39,%40,%41,%42,%43,%44,%45,%46,%47,%48,%49,%50,%51,%52,%53,%54,%55}, %56, %57, p, 1, 1, 0, 0;\n}\n"
    : "+f"(d[0]),"+f"(d[1]),"+f"(d[2]),"+f"(d[3]),"+f"(d[4]),"+f"(d[5]),"+f"(d[6]),"+f"(d[7]),"+f"(d[8]),"+f"(d[9]),"+f"(d[10]),"+f"(d[11]),"+f"(d[12]),"+f"(d[13]),"+f"(d[14]),"+f"(d[15]),"+f"(d[16]),"+f"(d[17]),"+f"(d[18]),"+f"(d[19]),"+f"(d[20]),"+f"(d[21]),"+f"(d[22]),"+f"(d[23]),"+f"(d[24]),"+f"(d[25]),"+f"(d[26]),"+f"(d[27]),"+f"(d[28]),"+f"(d[29]),"+f"(d[30]),"+f"(d[31]),"+f"(d[32]),"+f"(d[33]),"+f"(d[34]),"+f"(d[35]),"+f"(d[36]),"+f"(d[37]),"+f"(d[38]),"+f"(d[39]),"+f"(d[40]),"+f"(d[41]),"+f"(d[42]),"+f"(d[43]),"+f"(d[44]),"+f"(d[45]),"+f"(d[46]),"+f"(d[47]),"+f"(d[48]),"+f"(d[49]),"+f"(d[50]),"+f"(d[51]),"+f"(d[52]),"+f"(d[53]),"+f"(d[54]),"+f"(d[55])
    : "l"(descA), "l"(descB), "r"(scaleD));
}
__device__ __forceinline__ void wgmma_ss_n112_ta(float* d, uint64_t descA, uint64_t descB, int scaleD) {
  asm volatile("{\n.reg .pred p;\nsetp.ne.b32 p, %58, 0;\n"
    "wgmma.mma_async.sync.aligned.m64n112k16.f32.bf16.bf16 {%0,%1,%2,%3,%4,%5,%6,%7,%8,%9,%10,%11,%12,%13,%14,%15,%16,%17,%18,%19,%20,%21,%22,%23,%24,%25,%26,%27,%28,%29,%30,%31,%32,%33,%34,%35,%36,%37,%38,%39,%40,%41,%42,%43,%44,%45,%46,%47,%48,%49,%50,%51,%52,%53,%54,%55}, %56, %57, p, 1, 1, 1, 0;\n}\n"
    : "+f"(d[0]),"+f"(d[1]),"+f"(d[2]),"+f"(d[3]),"+f"(d[4]),"+f"(d[5]),"+f"(d[6]),"+f"(d[7]),"+f"(d[8]),"+f"(d[9]),"+f"(d[10]),"+f"(d[11]),"+f"(d[12]),"+f"(d[13]),"+f"(d[14]),"+f"(d[15]),"+f"(d[16]),"+f"(d[17]),"+f"(d[18]),"+f"(d[19]),"+f"(d[20]),"+f"(d[21]),"+f"(d[22]),"+f"(d[23]),"+f"(d[24]),"+f"(d[25]),"+f"(d[26]),"+f"(d[27]),"+f"(d[28]),"+f"(d[29]),"+f"(d[30]),"+f"(d[31]),"+f"(d[32]),"+f"(d[33]),"+f"(d[34]),"+f"(d[35]),"+f"(d[36]),"+f"(d[37]),"+f"(d[38]),"+f"(d[39]),"+f"(d[40]),"+f"(d[41]),"+f"(d[42]),"+f"(d[43]),"+f"(d[44]),"+f"(d[45]),"+f"(d[46]),"+f"(d[47]),"+f"(d[48]),"+f"(d[49]),"+f"(d[50]),"+f"(d[51]),"+f"(d[52]),"+f"(d[53]),"+f"(d[54]),"+f"(d[55])
    : "l"(descA), "l"(descB), "r"(scaleD));
}
__device__ __forceinline__ void wgmma_rs_n32(float* d, const uint32_t* a, uint64_t descB, int scaleD) {
  asm volatile("{\n.reg .pred p;\nsetp.ne.b32 p, %21, 0;\n"
    "wgmma.mma_async.sync.aligned.m64n32k16.f32.bf16.bf16 {%0,%1,%2,%3,%4,%5,%6,%7,%8,%9,%10,%11,%12,%13,%14,%15}, {%16,%17,%18,%19}, %20, p, 1, 1, 0;\n}\n"
    : "+f"(d[0]),"+f"(d[1]),"+f"(d[2]),"+f"(d[3]),"+f"(d[4]),"+f"(d[5]),"+f"(d[6]),"+f"(d[7]),"+f"(d[8]),"+f"(d[9]),"+f"(d[10]),"+f"(d[11]),"+f"(d[12]),"+f"(d[13]),"+f"(d[14]),"+f"(d[15])
    : "r"(a[0]), "r"(a[1]), "r"(a[2]), "r"(a[3]), "l"(descB), "r"(scaleD));
}
__device__ __forceinline__ void wgmma_ss_n128(float* d, uint64_t descA, uint64_t descB, int scaleD) {
  asm volatile("{\n.reg .pred p;\nsetp.ne.b32 p, %66, 0;\n"
    "wgmma.mma_async.sync.aligned.m64n128k16.f32.bf16.bf16 {%0,%1,%2,%3,%4,%5,%6,%7,%8,%9,%10,%11,%12,%13,%14,%15,%16,%17,%18,%19,%20,%21,%22,%23,%24,%25,%26,%27,%28,%29,%30,%31,%32,%33,%34,%35,%36,%37,%38,%39,%40,%41,%42,%43,%44,%45,%46,%47,%48,%49,%50,%51,%52,%53,%54,%55,%56,%57,%58,%59,%60,%61,%62,%63}, %64, %65, p, 1, 1, 0, 0;\n}\n"
    : "+f"(d[0]),"+f"(d[1]),"+f"(d[2]),"+f"(d[3]),"+f"(d[4]),"+f"(d[5]),"+f"(d[6]),"+f"(d[7]),"+f"(d[8]),"+f"(d[9]),"+f"(d[10]),"+f"(d[11]),"+f"(d[12]),"+f"(d[13]),"+f"(d[14]),"+f"(d[15]),"+f"(d[16]),"+f"(d[17]),"+f"(d[18]),"+f"(d[19]),"+f"(d[20]),"+f"(d[21]),"+f"(d[22]),"+f"(d[23]),"+f"(d[24]),"+f"(d[25]),"+f"(d[26]),"+f"(d[27]),"+f"(d[28]),"+f"(d[29]),"+f"(d[30]),"+f"(d[31]),"+f"(d[32]),"+f"(d[33]),"+f"(d[34]),"+f"(d[35]),"+f"(d[36]),"+f"(d[37]),"+f"(d[38]),"+f"(d[39]),"+f"(d[40]),"+f"(d[41]),"+f"(d[42]),"+f"(d[43]),"+f"(d[44]),"+f"(d[45]),"+f"(d[46]),"+f"(d[47]),"+f"(d[48]),"+f"(d[49]),"+f"(d[50]),"+f"(d[51]),"+f"(d[52]),"+f"(d[53]),"+f"(d[54]),"+f"(d[55]),"+f"(d[56]),"+f"(d[57]),"+f"(d[58]),"+f"(d[59]),"+f"(d[60]),"+f"(d[61]),"+f"(d[62]),"+f"(d[63])
    : "l"(descA), "l"(descB), "r"(scaleD));
}
__device__ __forceinline__ void wgmma_ss_n40(float* d, uint64_t descA, uint64_t descB, int scaleD) {
  asm volatile("{\n.reg .pred p;\nsetp.ne.b32 p, %22, 0;\n"
    "wgmma.mma_async.sync.aligned.m64n40k16.f32.bf16.bf16 {%0,%1,%2,%3,%4,%5,%6,%7,%8,%9,%10,%11,%12,%13,%14,%15,%16,%17,%18,%19}, %20, %21, p, 1, 1, 0, 0;\n}\n"
    : "+f"(d[0]),"+f"(d[1]),"+f"(d[2]),"+f"(d[3]),"+f"(d[4]),"+f"(d[5]),"+f"(d[6]),"+f"(d[7]),"+f"(d[8]),"+f"(d[9]),"+f"(d[10]),"+f"(d[11]),"+f"(d[12]),"+f"(d[13]),"+f"(d[14]),"+f"(d[15]),"+f"(d[16]),"+f"(d[17]),"+f"(d[18]),"+f"(d[19])
    : "l"(descA), "l"(descB), "r"(scaleD));
}
__device__ __forceinline__ void wgmma_ss_n32_ta(float* d, uint64_t descA, uint64_t descB, int scaleD) {
  asm volatile("{\n.reg .pred p;\nsetp.ne.b32 p, %18, 0;\n"
    "wgmma.mma_async.sync.aligned.m64n32k16.f32.bf16.bf16 {%0,%1,%2,%3,%4,%5,%6,%7,%8,%9,%10,%11,%12,%13,%14,%15}, %16, %17, p, 1, 1, 1, 0;\n}\n"
    : "+f"(d[0]),"+f"(d[1]),"+f"(d[2]),"+f"(d[3]),"+f"(d[4]),"+f"(d[5]),"+f"(d[6]),"+f"(d[7]),"+f"(d[8]),"+f"(d[9]),"+f"(d[10]),"+f"(d[11]),"+f"(d[12]),"+f"(d[13]),"+f"(d[14]),"+f"(d[15])
    : "l"(descA), "l"(descB), "r"(scaleD));
}
struct ChainArgs {
  const bf16* mem0;
  uint32_t* Mg;
  float4* Sg;
  uint32_t* flag;
  uint32_t* dbg;
};

constexpr int XT_BYTES = 28672;
constexpr int STG_BYTES = 5120;
constexpr int OFF_A = 0, OFF_B = 65536, OFF_C = OFF_B + 3 * XT_BYTES, OFF_M = OFF_C + 2 * XT_BYTES, OFF_P = OFF_M + 2 * 7168,
              OFF_SX = OFF_P + 4096, OFF_SM = OFF_SX + 2048, OFF_SW = OFF_SM + 512, OFF_BAR = OFF_SW + 1024, OFF_DBG = OFF_B + 2 * XT_BYTES + 3 * 7168, SMEM_CHAIN = OFF_BAR + 512;
enum { B_PA = 0, B_PE = 1, B_XF = 4, B_MB = 9, B_SX = 11, B_SM = 13, B_PB = 15, B_KR = 17, B_ST = 21, B_PF = 29, B_RD = 45, B_MF = 47, B_EM = 51, B_SB = 55, B_PE5 = 56, B_NUM = 61 };
#define MREP 1
#define MD0 320
#define MDELTA 800
#define SSTART 800
#define SXSTART 500
#define SSTAG 130
constexpr float L2E = 1.4426950408889634f;
constexpr int CHAIN_THREADS = 512;
#define TOKK 28

__device__ __forceinline__ uint32_t xstage_off(int st) { return st < 2 ? OFF_C + st * XT_BYTES : OFF_B + (st - 2) * XT_BYTES; }
__device__ __forceinline__ uint32_t mslot_off(int k) { return k < 3 ? OFF_B + 2 * XT_BYTES + k * 7168 : OFF_M; }
constexpr int OFF_VAR = OFF_BAR + 496;

__device__ __forceinline__ bool slot_has_sentinel(const uint8_t* p, int lane) {
  bool bad = false;
#pragma unroll 2
  for (int i = 0; i < 14; i++) { const uint4 v = *reinterpret_cast<const uint4*>(p + (32 * i + lane) * 16); bad |= (v.x == ~0u) | (v.y == ~0u) | (v.z == ~0u) | (v.w == ~0u); }
  return __any_sync(~0u, bad);
}
__device__ __forceinline__ uint32_t clk32() { uint32_t c; asm volatile("mov.u32 %0, %%clock;" : "=r"(c)); return c; }
__device__ __forceinline__ void wait_until(uint32_t t, uint32_t saddr) {
  while ((int)(clk32() - t) < 0) { uint32_t d; asm volatile("ld.volatile.shared.u32 %0, [%1];" : "=r"(d) : "r"(saddr) : "memory"); asm volatile("" ::"r"(d)); if (d == 0x12345u) break; }
}
#define DBG(slot) do {} while (0)
#define DBGV(slot, v) do {} while (0)

#define PDBG(i) do {} while (0)

template <bool CL>
__device__ __forceinline__ void issue_x_load(uint32_t sb, const CUtensorMap* tm_x, const CUtensorMap* tm_x3, int seg, int rank) {
  const int st = seg & 3;
  const uint32_t bar = sb + OFF_BAR + (B_XF + st) * 8;
  const uint32_t dst = sb + xstage_off(st);
  mbar_expect_tx(bar, XT_BYTES);
  if (CL) {
    if (rank < NJ) tma_load_2d_mc(dst + rank * 4096, tm_x, rank * 64, seg * SEG, bar, (uint16_t)0xFFFF);
  } else {
    tma_load_3d(dst, tm_x3, 0, seg * SEG, 0, bar);
  }
}

template <int WG>
__device__ __forceinline__ void tile_prologue(uint32_t* W, uint32_t sb) {
  const uint32_t bar = sb + OFF_BAR;
  const int lane = threadIdx.x & 31;
  float acc[112];
  mbar_wait(bar + B_PA * 8, 0);
#pragma unroll
  for (int half = 0; half < 2; half++) {
#pragma unroll
    for (int ec = 0; ec < 4; ec++) {
      const int i = half * 8 + ec * 2 + WG;
      const int st = i % 5;
      mbar_wait(bar + (B_PF + i) * 8, 0);
      const uint32_t bb = sb + OFF_B + st * XT_BYTES;
      wg_fence();
#pragma unroll
      for (int kk = 0; kk < 4; kk++) {
        if (WG == 0) {
          wgmma_ss_n112(acc, desc_sw128(sb + OFF_A + ec * 8192 + kk * 32), desc_sw128(bb + kk * 32), (ec | kk) != 0);
          wgmma_ss_n112(acc + 56, desc_sw128(sb + OFF_A + ec * 8192 + kk * 32), desc_sw128(bb + 14336 + kk * 32), (ec | kk) != 0);
        } else {
          wgmma_ss_n112_ta(acc, desc_sw128(sb + OFF_A + 32768 + (ec * 64 + kk * 16) * 128), desc_sw128(bb + kk * 32), (ec | kk) != 0);
          wgmma_ss_n112_ta(acc + 56, desc_sw128(sb + OFF_A + 32768 + (ec * 64 + kk * 16) * 128), desc_sw128(bb + 14336 + kk * 32), (ec | kk) != 0);
        }
      }
      wg_commit();
      wg_wait<0>();
      if (lane == 0) mbar_arrive(bar + (B_PE5 + st) * 8);
    }
    const float sc = WG == 0 ? 0.0625f : 1.0f;
#pragma unroll
    for (int kk = 0; kk < 14; kk++) {
      W[half * 56 + kk * 4 + 0] = pack_bf16(acc[8 * kk + 0] * sc, acc[8 * kk + 1] * sc);
      W[half * 56 + kk * 4 + 1] = pack_bf16(acc[8 * kk + 2] * sc, acc[8 * kk + 3] * sc);
      W[half * 56 + kk * 4 + 2] = pack_bf16(acc[8 * kk + 4] * sc, acc[8 * kk + 5] * sc);
      W[half * 56 + kk * 4 + 3] = pack_bf16(acc[8 * kk + 6] * sc, acc[8 * kk + 7] * sc);
    }
  }
}

__device__ __forceinline__ void token_gemm(const uint32_t* W, uint32_t sb, int seg, uint32_t stg_base, int w, int lane) {
  const int st = seg & 3;
  mbar_wait(sb + OFF_BAR + (B_XF + st) * 8, (seg >> 2) & 1);
  const uint32_t xb = sb + xstage_off(st);
  float d[16];
  wg_fence();
#pragma unroll
  for (int kk = 0; kk < TOKK; kk++) wgmma_rs_n32(d, &W[4 * kk], desc_sw128(xb + (kk >> 2) * 4096 + (kk & 3) * 32), kk != 0);
  wg_commit();
  wg_wait<0>();
  const uint32_t stg = stg_base + (seg & 3) * STG_BYTES + 1024;
  const int r = lane & 7, mi = lane >> 3;
#pragma unroll
  for (int p = 0; p < 2; p++) {
    const int t = 8 * (2 * p + (mi >> 1)) + r;
    const int chunk = 2 * w + (mi & 1);
    const uint32_t addr = stg + t * 128 + ((chunk ^ r) << 4);
    stsm_x4_t(addr, pack_bf16(d[8 * p + 0], d[8 * p + 1]), pack_bf16(d[8 * p + 2], d[8 * p + 3]), pack_bf16(d[8 * p + 4], d[8 * p + 5]),
              pack_bf16(d[8 * p + 6], d[8 * p + 7]));
  }
}

__device__ __forceinline__ void poll_smm(uint8_t* smem, uint32_t bar, const float4* src, int s, int p, int lane) {
  volatile uint32_t* var = reinterpret_cast<volatile uint32_t*>(smem + OFF_VAR);
  { int it = 0; while (var[1] != (uint32_t)s && ++it < SPIN_LIMIT) __nanosleep(20); }
  const uint32_t tM = clk32();
  wait_until(tM + SSTART + p * SSTAG, bar - OFF_BAR + OFF_VAR + 12);
  uint4 v; int it = 0; bool mine = true;
  while (true) {
    v = ld_vol_v4(src);
    if (__all_sync(~0u, __uint_as_float(v.z) == 7.f)) break;
    if (mbar_test(bar + (B_SM + (s & 1)) * 8, (s >> 1) & 1)) { mine = false; break; }
    if (++it > SPIN_LIMIT) break;
  }
  if (mine) {
    reinterpret_cast<float2*>(smem + OFF_SM + (s & 1) * 256)[lane] = make_float2(__uint_as_float(v.x), __uint_as_float(v.y));
    __syncwarp();
    if (lane == 0) { if (atomicExch(reinterpret_cast<uint32_t*>(smem + OFF_VAR), (uint32_t)(s + 1)) != (uint32_t)(s + 1)) mbar_arrive(bar + (B_SM + (s & 1)) * 8); }
  }
}

template <bool CL>
__global__ void __launch_bounds__(CHAIN_THREADS, 1)
chain_kernel(const __grid_constant__ CUtensorMap tm_x, const __grid_constant__ CUtensorMap tm_wq, const __grid_constant__ CUtensorMap tm_wk,
             const __grid_constant__ CUtensorMap tm_wv, const __grid_constant__ CUtensorMap tm_wo, const __grid_constant__ CUtensorMap tm_k,
             const __grid_constant__ CUtensorMap tm_y, const __grid_constant__ CUtensorMap tm_x3, ChainArgs args) {
  extern __shared__ __align__(1024) uint8_t smem[];
  const uint32_t sb = smem_u32(smem);
  const int tid = threadIdx.x, warp = tid >> 5, lane = tid & 31;
  const int j = blockIdx.x >> 4, h = blockIdx.x & 15;
  const uint32_t bar = sb + OFF_BAR;
  const int g = lane >> 2, q = lane & 3;
  KT_START(0);

  if (tid == 0) {
    mbar_init(bar + B_PA * 8, 1);
    for (int i = 0; i < 5; i++) mbar_init(bar + (B_PE5 + i) * 8, 4);
    for (int i = 0; i < 16; i++) mbar_init(bar + (B_PF + i) * 8, 1);
    for (int i = 0; i < 5; i++) mbar_init(bar + (B_XF + i) * 8, 1);
    for (int i = 0; i < 2; i++) {
      mbar_init(bar + (B_SX + i) * 8, 4); mbar_init(bar + (B_SM + i) * 8, 1); mbar_init(bar + (B_PB + i) * 8, 1); mbar_init(bar + (B_RD + i) * 8, 1);
    }
    for (int i = 0; i < 4; i++) { mbar_init(bar + (B_KR + i) * 8, 4); mbar_init(bar + (B_MF + i) * 8, 1); mbar_init(bar + (B_EM + i) * 8, 4); }
    mbar_init(bar + B_SB * 8, 1);
    for (int i = 0; i < 8; i++) mbar_init(bar + (B_ST + i) * 8, 4);
    asm volatile("fence.mbarrier_init.release.cluster;" ::: "memory");
  }
  __syncthreads();
  if (CL) cluster_sync_all();
  asm volatile("griddepcontrol.launch_dependents;" ::: "memory");
  PDBG(0);

  const int wgi = __shfl_sync(0xffffffffu, tid >> 7, 0);
  if (wgi < 2) {
    asm volatile("setmaxnreg.inc.sync.aligned.u32 200;");
    const int wg = wgi, w = warp & 3;
    uint32_t W[112];
    mbar_wait(bar + B_PA * 8, 0);
    PDBG(1);
    mbar_wait(bar + B_PF * 8, 0);
    PDBG(2);
    if (wg == 0) tile_prologue<0>(W, sb); else tile_prologue<1>(W, sb);
    PDBG(3);
    named_bar(0, CHAIN_THREADS);
    PDBG(4);
    PDBG(5);

    const uint32_t stg_base = sb + OFF_A + wg * 4 * STG_BYTES;
    token_gemm(W, sb, 0, stg_base, w, lane);
    PDBG(6);
    PDBG(7);
    __syncwarp();
    if (wg == 0 && lane == 0) mbar_arrive(bar + (B_KR + 0) * 8);

    if (wg == 0) {
      for (int s = 0; s < NSEG; s++) {
        float d0, d1, d2, d3;
        uint32_t ma[2];
        volatile uint32_t* var = reinterpret_cast<volatile uint32_t*>(smem + OFF_VAR);
        mbar_wait(bar + B_SB * 8, s & 1);
        uint32_t n = var[3];
        const uint32_t n_first = n;
        while (true) {
          const int slot = n & 3;
          mbar_wait(bar + (B_MF + slot) * 8, (n >> 2) & 1);
          if (tid == 0) DBG(0);
          const uint32_t ms = sb + mslot_off(slot);
          float a4[4][4];
#pragma unroll
          for (int i = 0; i < 4; i++) { a4[i][0] = a4[i][1] = a4[i][2] = a4[i][3] = 0.f; }
          uint32_t b[14][4];
#pragma unroll
          for (int i = 0; i < 14; i++) ldsm_x4_t(b[i], ms + (32 * i + lane) * 16);
          ldsm_x2_t(ma, ms + (64 * j + 16 * w + (lane & 15)) * 16);
#pragma unroll
          for (int i = 0; i < 14; i++) {
            mma16816(a4[(2 * i) & 3], W[8 * i + 0], W[8 * i + 1], W[8 * i + 2], W[8 * i + 3], b[i][0], b[i][1]);
            mma16816(a4[(2 * i + 1) & 3], W[8 * i + 4], W[8 * i + 5], W[8 * i + 6], W[8 * i + 7], b[i][2], b[i][3]);
          }
          d0 = (a4[0][0] + a4[1][0]) + (a4[2][0] + a4[3][0]); d1 = (a4[0][1] + a4[1][1]) + (a4[2][1] + a4[3][1]);
          d2 = (a4[0][2] + a4[1][2]) + (a4[2][2] + a4[3][2]); d3 = (a4[0][3] + a4[1][3]) + (a4[2][3] + a4[3][3]);
          if (!__any_sync(~0u, (d0 != d0) | (d1 != d1))) break;
          if (!slot_has_sentinel(smem + mslot_off(slot), lane)) break;
          if (n - n_first > (uint32_t)SPIN_LIMIT) break;
          if (lane == 0) mbar_arrive(bar + (B_EM + slot) * 8);
          n++;
        }
        if (tid == 0) { var[2] = n; var[1] = s; DBGV(14, n - n_first); }
        asm volatile("bar.arrive 5, 256;" ::: "memory");
        if (tid == 0) { asm volatile("" :: "f"(d0), "f"(d3)); DBG(8); }
        const uint32_t kb0 = movm_t(pack_bf16(d0, d1)), kb1 = movm_t(pack_bf16(d2, d3));
        if (s < NSEG - 1) {
          float c[4] = {0.f, 0.f, 0.f, 0.f};
          mma16816(c, ma[0], 0u, ma[1], 0u, kb0, kb1);
          float2* sw = reinterpret_cast<float2*>(smem + OFF_SW);
          sw[w * 32 + lane] = make_float2(c[0], c[1]);
          if (tid == 0) DBG(9);
          named_bar(1, 128);
          if (tid == 0) DBG(10);
          if (w == 0) {
            const float2 v0 = sw[lane], v1 = sw[32 + lane], v2 = sw[64 + lane], v3 = sw[96 + lane];
            red_v4(args.Sg + (((size_t)s * NH + h) * 5 + 4) * 32 + lane, (v0.x + v1.x) + (v2.x + v3.x), (v0.y + v1.y) + (v2.y + v3.y), 1.f, 0.f);
          }
        }
        asm volatile("bar.arrive 3, 256;" ::: "memory");
        if (tid == 0) DBG(1);
        {
          const uint32_t stg = stg_base + (s & 3) * STG_BYTES + g * 128 + q * 4;
          asm volatile("st.shared.u32 [%0], %1;" ::"r"(stg + (((2 * w) ^ g) << 4)), "r"(kb0) : "memory");
          asm volatile("st.shared.u32 [%0], %1;" ::"r"(stg + (((2 * w + 1) ^ g) << 4)), "r"(kb1) : "memory");
          fence_async_smem();
          __syncwarp();
          if (lane == 0) mbar_arrive(bar + (B_ST + (s & 3)) * 8);
        }
        if (s + 1 < NSEG) {
          token_gemm(W, sb, s + 1, stg_base, w, lane);
          __syncwarp();
          if (lane == 0) mbar_arrive(bar + (B_KR + ((s + 1) & 3)) * 8);
        }
        if (tid == 0) DBG(11);
        named_bar(1, 128);
      }
    } else {
      const int hd = w * 4 + (lane >> 3);
      uint32_t p_dst = sb + OFF_P + h * 128 + (lane & 7) * 16, p_bar = bar + B_PB * 8;
      if (CL) { p_dst = mapa(p_dst, hd); p_bar = mapa(p_bar, hd); }
      const uint32_t ONE2 = 0x3F803F80u;
      for (int s = 0; s < NSEG; s++) {
        if (s < NSEG - 1) {
          mbar_wait(bar + (B_KR + (s & 3)) * 8, (s >> 2) & 1);
          const uint32_t kst = sb + OFF_A + (s & 3) * STG_BYTES + 1024;
          uint32_t bk[2][4];
#pragma unroll
          for (int i = 0; i < 2; i++) ldsm_x4(bk[i], kst + (8 * w + (lane & 7)) * 128 + (((4 * i + (lane >> 3)) ^ (lane & 7)) << 4));
          float c[4], c2[4];
          volatile uint32_t* var = reinterpret_cast<volatile uint32_t*>(smem + OFF_VAR);
          mbar_wait(bar + B_SB * 8, s & 1);
          uint32_t n = var[3];
          mbar_wait(bar + (B_MF + (n & 3)) * 8, (n >> 2) & 1);
          bool synced = false;
          while (true) {
            const uint32_t ms = sb + mslot_off(n & 3);
            c[0] = c[1] = c[2] = c[3] = 0.f; c2[0] = c2[1] = c2[2] = c2[3] = 0.f;
            uint32_t a[2][4];
            ldsm_x4_t(a[0], ms + (64 * j + lane) * 16);
            ldsm_x4_t(a[1], ms + (64 * j + 32 + lane) * 16);
            mma16816(c, a[0][0], 0u, a[0][1], 0u, bk[0][0], bk[0][1]);
            mma16816(c2, a[0][2], 0u, a[0][3], 0u, bk[0][2], bk[0][3]);
            mma16816(c, a[1][0], 0u, a[1][1], 0u, bk[1][0], bk[1][1]);
            mma16816(c2, a[1][2], 0u, a[1][3], 0u, bk[1][2], bk[1][3]);
            c[0] += c2[0]; c[1] += c2[1];
            if (synced || !__any_sync(~0u, (c[0] != c[0]) | (c[1] != c[1]))) break;
            named_bar(5, 256);
            synced = true;
            n = var[2];
          }
          red_v4(args.Sg + (((size_t)s * NH + h) * 5 + w) * 32 + lane, c[0], c[1], 1.f, 0.f);
          if (!synced) named_bar(5, 256);
        } else named_bar(5, 256);
        named_bar(3, 256);
        const uint32_t ms = sb + mslot_off(reinterpret_cast<volatile uint32_t*>(smem + OFF_VAR)[2] & 3);
        float a4[4][4];
#pragma unroll
        for (int i = 0; i < 4; i++) { a4[i][0] = a4[i][1] = a4[i][2] = a4[i][3] = 0.f; }
        {
          uint32_t b[14][4];
#pragma unroll
          for (int i = 0; i < 14; i++) ldsm_x4_t(b[i], ms + (32 * i + lane) * 16);
#pragma unroll
          for (int i = 0; i < 14; i++) {
            mma16816(a4[(2 * i) & 3], W[8 * i + 0], W[8 * i + 1], W[8 * i + 2], W[8 * i + 3], b[i][0], b[i][1]);
            mma16816(a4[(2 * i + 1) & 3], W[8 * i + 4], W[8 * i + 5], W[8 * i + 6], W[8 * i + 7], b[i][2], b[i][3]);
          }
        }
        const uint32_t za0 = pack_bf16((a4[0][0] + a4[1][0]) + (a4[2][0] + a4[3][0]), (a4[0][1] + a4[1][1]) + (a4[2][1] + a4[3][1]));
        const uint32_t za1 = pack_bf16((a4[0][2] + a4[1][2]) + (a4[2][2] + a4[3][2]), (a4[0][3] + a4[1][3]) + (a4[2][3] + a4[3][3]));
        {
          const uint32_t stg = stg_base + (s & 3) * STG_BYTES + g * 128 + q * 4;
          asm volatile("st.shared.u32 [%0], %1;" ::"r"(stg + (((2 * w) ^ g) << 4)), "r"(movm_t(za0)) : "memory");
          asm volatile("st.shared.u32 [%0], %1;" ::"r"(stg + (((2 * w + 1) ^ g) << 4)), "r"(movm_t(za1)) : "memory");
          fence_async_smem();
          __syncwarp();
          if (lane == 0) mbar_arrive(bar + (B_ST + 4 + (s & 3)) * 8);
        }
        if (s < NSEG - 1) {
          uint32_t va[2][4];
          const uint32_t vst = stg_base + (s & 3) * STG_BYTES + 1024;
#pragma unroll
          for (int kk = 0; kk < 2; kk++) {
            const int mi = lane >> 3, r = lane & 7;
            const int t = 8 * (2 * kk + (mi >> 1)) + r;
            ldsm_x4_t(va[kk], vst + t * 128 + (((2 * w + (mi & 1)) ^ r) << 4));
          }
          mbar_wait(bar + (B_SX + (s & 1)) * 8, (s >> 1) & 1);
          const float2* sx = reinterpret_cast<const float2*>(smem + OFF_SX + (s & 1) * 1024);
          float ex[8];
#pragma unroll
          for (int nt = 0; nt < 4; nt++) { const float2 v = sx[nt * 32 + lane]; ex[2 * nt] = v.x; ex[2 * nt + 1] = v.y; }
          float mx = fmaxf(fmaxf(fmaxf(ex[0], ex[1]), fmaxf(ex[2], ex[3])), fmaxf(fmaxf(ex[4], ex[5]), fmaxf(ex[6], ex[7])));
          mx = fmaxf(mx, __shfl_xor_sync(~0u, mx, 1));
          mx = fmaxf(mx, __shfl_xor_sync(~0u, mx, 2));
#pragma unroll
          for (int k = 0; k < 8; k++) ex[k] = ex2((ex[k] - mx) * L2E);
          mbar_wait(bar + (B_SM + (s & 1)) * 8, (s >> 1) & 1);
          if (tid == 128) DBG(2);
          const float2 sm = reinterpret_cast<const float2*>(smem + OFF_SM + (s & 1) * 256)[lane];
          float mm = fmaxf(sm.x, sm.y);
          mm = fmaxf(mm, __shfl_xor_sync(~0u, mm, 1));
          mm = fmaxf(mm, __shfl_xor_sync(~0u, mm, 2));
          const float m = fmaxf(mx, mm);
          const float f = ex2((mx - m) * L2E);
          const uint32_t pm = pack_bf16(ex2((sm.x - m) * L2E), ex2((sm.y - m) * L2E));
          uint32_t bx[4];
#pragma unroll
          for (int nt = 0; nt < 4; nt++) bx[nt] = pack_bf16(ex[2 * nt] * f, ex[2 * nt + 1] * f);
          float o0[4] = {0.f, 0.f, 0.f, 0.f}, o1[4] = {0.f, 0.f, 0.f, 0.f}, o2[4] = {0.f, 0.f, 0.f, 0.f};
          float l0[4] = {0.f, 0.f, 0.f, 0.f}, l1[4] = {0.f, 0.f, 0.f, 0.f}, l2[4] = {0.f, 0.f, 0.f, 0.f};
          mma1688(o0, za0, za1, pm);
          mma1688(l0, ONE2, ONE2, pm);
          mma16816(o1, va[0][0], va[0][1], va[0][2], va[0][3], bx[0], bx[1]);
          mma16816(l1, ONE2, ONE2, ONE2, ONE2, bx[0], bx[1]);
          mma16816(o2, va[1][0], va[1][1], va[1][2], va[1][3], bx[2], bx[3]);
          mma16816(l2, ONE2, ONE2, ONE2, ONE2, bx[2], bx[3]);
          const float r0 = __fdividef(1.f, l0[0] + l1[0] + l2[0]), r1 = __fdividef(1.f, l0[1] + l1[1] + l2[1]);
          const float v0 = (o0[0] + o1[0] + o2[0]) * r0, v1 = (o0[1] + o1[1] + o2[1]) * r1;
          const float v2 = (o0[2] + o1[2] + o2[2]) * r0, v3 = (o0[3] + o1[3] + o2[3]) * r1;
          if (CL) {
            st_async_v4(p_dst + (s & 1) * 2048, v0, v1, v2, v3, p_bar + (s & 1) * 8);
          } else {
            uint4* dst = reinterpret_cast<uint4*>(args.Sg + (size_t)NSEG * NH * 5 * 32) + ((((size_t)s * NJ + j) * 16 + hd) * 16 + h) * 8 + (lane & 7);
            uint32_t u0 = ~__float_as_uint(v0), u1 = ~__float_as_uint(v1), u2 = ~__float_as_uint(v2), u3 = ~__float_as_uint(v3);
            u0 += (u0 == 0); u1 += (u1 == 0); u2 += (u2 == 0); u3 += (u3 == 0);
            asm volatile("st.relaxed.gpu.global.v4.u32 [%0], {%1,%2,%3,%4};" ::"l"(dst), "r"(u0), "r"(u1), "r"(u2), "r"(u3) : "memory");
          }
          if (tid == 128) DBG(3);
        }
        if (s + 1 < NSEG) token_gemm(W, sb, s + 1, stg_base, w, lane);
        if (tid == 128) DBG(12);
      }
    }
  } else if (wgi == 2) {
    asm volatile("setmaxnreg.dec.sync.aligned.u32 80;");
    const int aw = warp - 8, at = tid - 256;
    named_bar(0, CHAIN_THREADS);
    for (int s = 0; s < NSEG; s++) {
      volatile uint32_t* var = reinterpret_cast<volatile uint32_t*>(smem + OFF_VAR);
      if (s == 0) {
        for (int c = at; c < DM; c += 128) {
          uint32_t v[4];
#pragma unroll
          for (int i = 0; i < 4; i++) {
            uint32_t lo = reinterpret_cast<const uint16_t*>(args.mem0)[(2 * i) * DM + c], hi = reinterpret_cast<const uint16_t*>(args.mem0)[(2 * i + 1) * DM + c];
            if (lo == 0xFFFFu) lo = 0x7FFFu;
            if (hi == 0xFFFFu) hi = 0x7FFFu;
            v[i] = lo | (hi << 16);
          }
          *reinterpret_cast<uint4*>(smem + mslot_off(0) + c * 16) = make_uint4(v[0], v[1], v[2], v[3]);
        }
        fence_async_smem();
        named_bar(2, 128);
        if (at == 0) mbar_arrive(bar + B_MF * 8);
      }
      { int it = 0; while (var[1] != (uint32_t)s && ++it < SPIN_LIMIT) __nanosleep(20); }
      if (j == 0) {
        const float4 z4 = make_float4(0.f, 0.f, 0.f, 0.f);
        if (s >= 2) { float4* p = args.Sg + ((size_t)(s - 2) * NH + h) * 160; p[aw * 32 + lane] = z4; if (aw == 0) p[128 + lane] = z4; }
        if (s == NSEG - 1) { float4* p = args.Sg + ((size_t)(s - 1) * NH + h) * 160; p[aw * 32 + lane] = z4; if (aw == 0) p[128 + lane] = z4; }
      }
      if (at == 32) DBG(4);
      if (s == NSEG - 1) break;
      const uint32_t tM = clk32();
      {
        const float4* src = args.Sg + (((size_t)s * NH + h) * 5 + aw) * 32 + lane;
        wait_until(tM + SXSTART, sb + OFF_VAR + 12);
        uint4 v; int it = 0;
        do { v = ld_vol_v4(src); } while (__uint_as_float(v.z) != 7.f && ++it < SPIN_LIMIT);
        reinterpret_cast<float2*>(smem + OFF_SX + (s & 1) * 1024)[aw * 32 + lane] = make_float2(__uint_as_float(v.x), __uint_as_float(v.y));
        __syncwarp();
        if (lane == 0) mbar_arrive(bar + (B_SX + (s & 1)) * 8);
        if (at == 0) DBG(13);
      }
    }
  } else {
    asm volatile("setmaxnreg.dec.sync.aligned.u32 32;");
    if (tid == 384) {
      reinterpret_cast<uint32_t*>(smem + OFF_VAR)[0] = 0; reinterpret_cast<uint32_t*>(smem + OFF_VAR)[1] = ~0u;
      mbar_expect_tx(bar + B_PA * 8, 65536);
#pragma unroll
      for (int ec = 0; ec < 4; ec++) tma_load_2d(sb + OFF_A + ec * 8192, &tm_wq, h * DH + ec * 64, 64 * j, bar + B_PA * 8);
      tma_load_2d(sb + OFF_A + 32768, &tm_wo, 64 * j, h * DH, bar + B_PA * 8);
      for (int i = 0; i < 16; i++) {
        const int st = i % 5, half = i >> 3, ec = (i & 7) >> 1;
        if (i >= 5) mbar_wait(bar + (B_PE5 + st) * 8, ((i / 5) - 1) & 1);
        mbar_expect_tx(bar + (B_PF + i) * 8, XT_BYTES);
        tma_load_2d(sb + OFF_B + st * XT_BYTES, (i & 1) ? &tm_wv : &tm_wk, h * DH + ec * 64, half * 224, bar + (B_PF + i) * 8);
      }
    }
    if (tid == 384) {
#pragma unroll 1
      for (int sg = 0; sg < 2; sg++) {
        mbar_wait(bar + (B_PE5 + 3 + sg) * 8, 0);
        mbar_expect_tx(bar + (B_XF + sg) * 8, XT_BYTES);
        tma_load_3d(sb + xstage_off(sg), &tm_x3, 0, sg * SEG, 0, bar + (B_XF + sg) * 8);
      }
    }
    if (warp == 13 && !(lane & 1)) {
      const int l8 = lane >> 2, v = lane & 3;
      const int c = 16 * (h >> 2) + 2 * (h & 3) + (l8 >> 2) + (v >> 1) * 8;
      for (int s = 1; s < NSEG; s++)
#pragma unroll
        for (int r = 0; r < MREP; r++) st_relaxed(args.Mg + ((size_t)s * MREP + r) * 1792 + (64 * j + c) * 4 + (l8 & 3), 0xFFFFFFFFu);
      __threadfence();
    }
    __syncwarp();
    named_bar(0, CHAIN_THREADS);
    if (tid == 384) {
      issue_x_load<false>(sb, &tm_x, &tm_x3, 2, h);
      for (int s = 0; s < NSEG; s++) {
        mbar_wait(bar + (B_ST + (s & 3)) * 8, (s >> 2) & 1);
        tma_store_2d(&tm_k, 64 * j, (h * NSEG + s) * LKEY, sb + OFF_A + (s & 3) * STG_BYTES);
        mbar_wait(bar + (B_ST + 4 + (s & 3)) * 8, (s >> 2) & 1);
        tma_store_2d(&tm_y, 64 * j, (h * NSEG + s) * LKEY, sb + OFF_A + (4 + (s & 3)) * STG_BYTES);
        bulk_commit();
        if (s + 3 < NSEG) { if (s == 0) issue_x_load<false>(sb, &tm_x, &tm_x3, 3, h); else issue_x_load<CL>(sb, &tm_x, &tm_x3, s + 3, h); }
        bulk_wait<0>();
        fence_async_all();
        __threadfence();
        red_u32(args.flag + s, 1u);
      }
    } else if (warp == 13) {
      for (int s = 0; s < NSEG - 1; s++) {
        float acc;
        if (CL && lane == 0) mbar_expect_tx(bar + (B_PB + (s & 1)) * 8, 16 * 128);
        poll_smm(smem, bar, args.Sg + (((size_t)s * NH + h) * 5 + 4) * 32 + lane, s, 1, lane);
        if (CL) {
          mbar_wait_cluster(bar + (B_PB + (s & 1)) * 8, (s >> 1) & 1);
          if (lane == 0) DBG(5);
          const float* pin = reinterpret_cast<const float*>(smem + OFF_P + (s & 1) * 2048);
          float a0 = 0.f, a1 = 0.f, a2 = 0.f, a3 = 0.f;
#pragma unroll
          for (int k = 0; k < 16; k += 4) { a0 += pin[k * 32 + lane]; a1 += pin[(k + 1) * 32 + lane]; a2 += pin[(k + 2) * 32 + lane]; a3 += pin[(k + 3) * 32 + lane]; }
          acc = (a0 + a1) + (a2 + a3);
        } else {
          const uint32_t* src = reinterpret_cast<const uint32_t*>(args.Sg + (size_t)NSEG * NH * 5 * 32) + (((size_t)s * NJ + j) * 16 + h) * 16 * 32 + lane;
          acc = 0.f;
#pragma unroll 1
          for (int k = 0; k < 16; k += 4) {
            uint32_t v0, v1, v2, v3; int it = 0;
            do {
              asm volatile("ld.volatile.global.u32 %0, [%1];" : "=r"(v0) : "l"(src + k * 32) : "memory");
              asm volatile("ld.volatile.global.u32 %0, [%1];" : "=r"(v1) : "l"(src + k * 32 + 32) : "memory");
              asm volatile("ld.volatile.global.u32 %0, [%1];" : "=r"(v2) : "l"(src + k * 32 + 64) : "memory");
              asm volatile("ld.volatile.global.u32 %0, [%1];" : "=r"(v3) : "l"(src + k * 32 + 96) : "memory");
            } while ((v0 == 0u || v1 == 0u || v2 == 0u || v3 == 0u) && ++it < SPIN_LIMIT);
            acc += (__uint_as_float(~v0) + __uint_as_float(~v1)) + (__uint_as_float(~v2) + __uint_as_float(~v3));
            uint32_t* cl = const_cast<uint32_t*>(src) + k * 32;
            cl[0] = 0u; cl[32] = 0u; cl[64] = 0u; cl[96] = 0u;
          }
        }
        const float o = __shfl_down_sync(~0u, acc, 1);
        const uint32_t u = pack_bf16(acc, o);
        const int l8 = lane >> 2, v = lane & 3;
        const int c = 16 * (h >> 2) + 2 * (h & 3) + (l8 >> 2) + (v >> 1) * 8;
        if (!(lane & 1)) {
#pragma unroll
          for (int r = 0; r < MREP; r++) st_relaxed(args.Mg + ((size_t)(s + 1) * MREP + r) * 1792 + (64 * j + c) * 4 + (l8 & 3), u);
        }
        if (lane == 0) { DBG(6); mbar_arrive(bar + (B_RD + (s & 1)) * 8); }
      }
    } else if (warp == 15) {
      for (int s = 0; s < NSEG - 1; s++) poll_smm(smem, bar, args.Sg + (((size_t)s * NH + h) * 5 + 4) * 32 + lane, s, 0, lane);
    } else if (tid == 448) {
      volatile uint32_t* var = reinterpret_cast<volatile uint32_t*>(smem + OFF_VAR);
      uint32_t n = 0, empar = 0;
      for (int s = 0; s < NSEG; s++) {
        if (s > 0) mbar_wait(bar + (B_RD + ((s - 1) & 1)) * 8, ((s - 1) >> 1) & 1);
        const uint32_t n0 = n;
        var[3] = n0;
        mbar_arrive(bar + B_SB * 8);
        uint32_t tnext = clk32() + MD0;
        int it = 0;
        if (s == 0) n = 1;
        while (s > 0) {
          bool done = false;
          while ((int)(clk32() - tnext) < 0) { if (var[1] == (uint32_t)s) { done = true; break; } }
          if (done || var[1] == (uint32_t)s || ++it > SPIN_LIMIT) break;
          const int slot = n & 3;
          if (n - n0 >= 4) {
            int it2 = 0;
            while (!mbar_test(bar + (B_EM + slot) * 8, (empar >> slot) & 1)) { if (var[1] == (uint32_t)s || ++it2 > SPIN_LIMIT) { done = true; break; } }
            if (done) break;
            empar ^= 1u << slot;
          }
          mbar_expect_tx(bar + (B_MF + slot) * 8, 7168);
          bulk_load(sb + mslot_off(slot), args.Mg + ((size_t)s * MREP + (blockIdx.x % MREP)) * 1792, 7168, bar + (B_MF + slot) * 8);
          n++;
          tnext += MDELTA;
        }
        { int it3 = 0; while (var[1] != (uint32_t)s && ++it3 < SPIN_LIMIT) {} }
        const uint32_t ns = var[2];
        const uint32_t waited = n - n0 > 4 ? n - n0 - 4 : 0;
        for (uint32_t a = n0 + waited; a < ns; a++) empar ^= 1u << (a & 3);
        for (uint32_t a = ns + 1; a < n; a++) mbar_wait(bar + (B_MF + (a & 3)) * 8, (a >> 2) & 1);
        DBGV(15, n - n0);
      }
    }
    __syncwarp();
  }
  named_bar(0, CHAIN_THREADS);
  KT_END(0);
  if (CL) cluster_sync_all();
}
struct SsmArgs {
  const bf16 *lam_re, *lam_im, *log_dt, *dskip, *x, *gate_w;
  float* hloc;
  float2* hend;
  float* omg;
  float* gate;
  float4* tab;
  float* out;
};

__device__ __forceinline__ float bf2f(bf16 v) { return __bfloat162float(v); }
__device__ __forceinline__ float rbf(float v) { return __bfloat162float(__float2bfloat16_rn(v)); }
__device__ __forceinline__ float2 cmul(float2 a, float2 b) { return make_float2(a.x * b.x - a.y * b.y, a.x * b.y + a.y * b.x); }
__device__ __forceinline__ float2 ssm_z(const SsmArgs& a, int ch) {
  const float dt = rbf(expf(bf2f(a.log_dt[ch])));
  return make_float2(dt * bf2f(a.lam_re[ch]), dt * bf2f(a.lam_im[ch]));
}
__device__ __forceinline__ float2 cexp_n(float2 z, float n) {
  float sn, cs;
  sincosf(z.y * n, &sn, &cs);
  const float e = expf(z.x * n);
  return make_float2(e * cs, e * sn);
}

__global__ void __launch_bounds__(128) gate_kernel(SsmArgs args) {
  const int warp = threadIdx.x >> 5, lane = threadIdx.x & 31;
  const int t0 = blockIdx.x * 32 + warp * 8;
  float acc[8];
#pragma unroll
  for (int tt = 0; tt < 8; tt++) acc[tt] = 0.f;
#pragma unroll
  for (int d = 2 * lane; d < DM; d += 64) {
    const __nv_bfloat162 wv = *reinterpret_cast<const __nv_bfloat162*>(args.gate_w + d);
#pragma unroll
    for (int tt = 0; tt < 8; tt++) {
      const __nv_bfloat162 xv = *reinterpret_cast<const __nv_bfloat162*>(args.x + (size_t)(t0 + tt) * DM + d);
      acc[tt] += rbf(bf2f(xv.x) * bf2f(wv.x)) + rbf(bf2f(xv.y) * bf2f(wv.y));
    }
  }
#pragma unroll
  for (int tt = 0; tt < 8; tt++) {
#pragma unroll
    for (int o = 16; o; o >>= 1) acc[tt] += __shfl_xor_sync(~0u, acc[tt], o);
    if (lane == 0) {
      const float gv = rbf(1.f / (1.f + expf(-rbf(acc[tt]))));
      args.gate[t0 + tt] = gv;
      args.omg[t0 + tt] = rbf(1.f - gv);
    }
  }
}

constexpr int S1_STAGE = 32768, S1_NST = 3, S1_SMEM = S1_NST * S1_STAGE + 256;
__global__ void __launch_bounds__(160, 2)
ssm1_kernel(const __grid_constant__ CUtensorMap tm_bre, const __grid_constant__ CUtensorMap tm_bim, const __grid_constant__ CUtensorMap tm_xp, SsmArgs args) {
  extern __shared__ __align__(1024) uint8_t smem[];
  const uint32_t sb = smem_u32(smem), bar = sb + S1_NST * S1_STAGE;
  const int tid = threadIdx.x, warp = tid >> 5, lane = tid & 31;
  const int cg = blockIdx.x, tc = blockIdx.y;
  KT_START(1);
  if (tid == 0) {
    for (int i = 0; i < 7; i++) mbar_init(bar + i * 8, 1);
    for (int i = 0; i < 3; i++) mbar_init(bar + (8 + i) * 8, 4);
    asm volatile("fence.mbarrier_init.release.cluster;" ::: "memory");
  }
  __syncthreads();
  if (warp == 4) {
    if (lane == 0) {
      for (int kc = 0; kc < 7; kc++) {
        const int st = kc % 3;
        if (kc >= 3) mbar_wait(bar + (8 + st) * 8, ((kc / 3) - 1) & 1);
        mbar_expect_tx(bar + kc * 8, S1_STAGE);
        tma_load_2d(sb + st * S1_STAGE, &tm_bre, kc * 64, cg * 64, bar + kc * 8);
        tma_load_2d(sb + st * S1_STAGE + 8192, &tm_bim, kc * 64, cg * 64, bar + kc * 8);
        tma_load_4d(sb + st * S1_STAGE + 16384, &tm_xp, kc * 64, 0, tc * 4, 0, bar + kc * 8);
      }
    }
    return;
  }
  const int g = lane >> 2, q = lane & 3;
  float2 zz[2]; float lre[2], lim[2];
#pragma unroll
  for (int r = 0; r < 2; r++) { const int ch = cg * 64 + warp * 16 + g + r * 8; zz[r] = ssm_z(args, ch); lre[r] = bf2f(args.lam_re[ch]); lim[r] = bf2f(args.lam_im[ch]); }
  float ur[64], ui[64];
#pragma unroll 1
  for (int kc = 0; kc < 7; kc++) {
    const int st = kc % 3;
    mbar_wait(bar + kc * 8, 0);
    const uint32_t b0 = sb + st * S1_STAGE;
    wg_fence();
#pragma unroll
    for (int kk = 0; kk < 4; kk++) {
      wgmma_ss_n128(ur, desc_sw128(b0 + kk * 32), desc_sw128(b0 + 16384 + kk * 32), (kc | kk) != 0);
      wgmma_ss_n128(ui, desc_sw128(b0 + 8192 + kk * 32), desc_sw128(b0 + 16384 + kk * 32), (kc | kk) != 0);
    }
    wg_commit();
    wg_wait<0>();
    if (lane == 0) mbar_arrive(bar + (8 + st) * 8);
  }
#pragma unroll
  for (int r = 0; r < 2; r++) {
    const int ch = cg * 64 + warp * 16 + g + r * 8;
    const float2 z = zz[r];
    const float2 lam = cexp_n(z, 1.f);
    const float lr = lre[r], li = lim[r];
    const float den = lr * lr + li * li;
    const float2 num = make_float2(lam.x - 1.f, lam.y);
    const float2 coef = make_float2((num.x * lr + num.y * li) / den, (num.y * lr - num.x * li) / den);
    float2 hs = make_float2(0.f, 0.f);
#pragma unroll
    for (int i = 0; i < 32; i++) {
      const int idx = (i >> 1) * 4 + r * 2 + (i & 1);
      const float2 bu = cmul(coef, make_float2(ur[idx], ui[idx]));
      hs = make_float2(fmaf(lam.x, hs.x, fmaf(-lam.y, hs.y, bu.x)), fmaf(lam.x, hs.y, fmaf(lam.y, hs.x, bu.y)));
      ur[idx] = hs.x; ui[idx] = hs.y;
    }
    const float2 l32 = cexp_n(z, 32.f);
    if (tc == 0 && q == 0) {
      const float2 l128 = cexp_n(z, 128.f);
      args.tab[ch * 2] = make_float4(lam.x, lam.y, l32.x, l32.y);
      args.tab[ch * 2 + 1] = make_float4(l128.x, l128.y, 0.f, 0.f);
    }
    float2 carry = make_float2(0.f, 0.f);
#pragma unroll
    for (int qq = 0; qq < 3; qq++) {
      const float ex = __shfl_sync(~0u, hs.x, (lane & ~3) + qq), ey = __shfl_sync(~0u, hs.y, (lane & ~3) + qq);
      if (qq < q) { const float2 t = cmul(l32, carry); carry = make_float2(t.x + ex, t.y + ey); }
    }
    float2 p = lam;
    float4* dre = reinterpret_cast<float4*>(args.hloc) + ((((size_t)tc * 7 + cg) * 4 + warp) * 2 + r) * 256 + lane;
    float4* dim = dre + (size_t)DM * SEQ / 4;
#pragma unroll
    for (int i4 = 0; i4 < 8; i4++) {
      float vr[4], vi[4];
#pragma unroll
      for (int e = 0; e < 4; e++) {
        const int i = i4 * 4 + e, idx = (i >> 1) * 4 + r * 2 + (i & 1);
        const float2 t = cmul(p, carry);
        vr[e] = ur[idx] + t.x; vi[e] = ui[idx] + t.y;
        p = cmul(p, lam);
      }
      dre[i4 * 32] = make_float4(vr[0], vr[1], vr[2], vr[3]);
      dim[i4 * 32] = make_float4(vi[0], vi[1], vi[2], vi[3]);
      if (i4 == 7 && q == 3) args.hend[tc * DM + ch] = make_float2(vr[3], vi[3]);
    }
  }
  KT_END(1);
}

constexpr int S2_A = 896 * 128, S2_NST = 3, S2_SMEM = S2_A + S2_NST * XT_BYTES + 1024;
__global__ void __launch_bounds__(288, 1)
ssm2_kernel(const __grid_constant__ CUtensorMap tm_cre, const __grid_constant__ CUtensorMap tm_cim, SsmArgs args) {
  extern __shared__ __align__(1024) uint8_t smem[];
  const uint32_t sb = smem_u32(smem), bar = sb + S2_A + S2_NST * XT_BYTES;
  float* sg = reinterpret_cast<float*>(smem + S2_A + S2_NST * XT_BYTES + 512);
  const int tid = threadIdx.x, warp = tid >> 5, lane = tid & 31;
  const int t0 = blockIdx.x * 64, chunk = t0 >> 7, tau0 = t0 & 127;
  KT_START(2);
  if (tid == 0) {
    for (int i = 0; i < 28; i++) mbar_init(bar + i * 8, 1);
    for (int i = 0; i < 3; i++) mbar_init(bar + (28 + i) * 8, 4);
    asm volatile("fence.mbarrier_init.release.cluster;" ::: "memory");
  }
  __syncthreads();
  if (warp == 8) {
    if (lane == 0) {
      for (int i = 0; i < 28; i++) {
        const int st = i % 3, kc = i >> 1;
        if (i >= 3) mbar_wait(bar + (28 + st) * 8, ((i / 3) - 1) & 1);
        mbar_expect_tx(bar + i * 8, XT_BYTES);
        tma_load_2d(sb + S2_A + st * XT_BYTES, kc < 7 ? &tm_cre : &tm_cim, (kc % 7) * 64, (i & 1) * 224, bar + i * 8);
      }
    }
    return;
  }
  if (tid < 64) sg[tid] = args.gate[t0 + tid];
  for (int it = tid; it < DM * 2; it += 256) {
    const int qi = it & 1, gg = (it >> 1) & 7, r = (it >> 4) & 1, cw = it >> 5;
    const int ch = cw * 16 + r * 8 + gg;
    const float4 tb0 = args.tab[ch * 2], tb1 = args.tab[ch * 2 + 1];
    float2 e[15];
#pragma unroll
    for (int c = 0; c < 15; c++) e[c] = c < chunk ? args.hend[c * DM + ch] : make_float2(0.f, 0.f);
    const int qq = (tau0 >> 5) + qi;
    const float4* sre = reinterpret_cast<const float4*>(args.hloc) + (((size_t)chunk * 28 + cw) * 2 + r) * 256 + gg * 4 + qq;
    const float4* sim = sre + (size_t)DM * SEQ / 4;
    float4 vr4[8], vi4[8];
#pragma unroll
    for (int i4 = 0; i4 < 8; i4++) { vr4[i4] = sre[i4 * 32]; vi4[i4] = sim[i4 * 32]; }
    const float2 l128 = make_float2(tb1.x, tb1.y), lam = make_float2(tb0.x, tb0.y), l32 = make_float2(tb0.z, tb0.w);
    float2 hin = make_float2(0.f, 0.f);
#pragma unroll
    for (int c = 0; c < 15; c++) if (c < chunk) { const float2 t = cmul(l128, hin); hin = make_float2(t.x + e[c].x, t.y + e[c].y); }
    float2 p = cmul(lam, hin);
    for (int k = 0; k < qq; k++) p = cmul(p, l32);
#pragma unroll
    for (int m = 0; m < 4; m++) {
      float vr[8] = {vr4[2 * m].x, vr4[2 * m].y, vr4[2 * m].z, vr4[2 * m].w, vr4[2 * m + 1].x, vr4[2 * m + 1].y, vr4[2 * m + 1].z, vr4[2 * m + 1].w};
      float vi[8] = {vi4[2 * m].x, vi4[2 * m].y, vi4[2 * m].z, vi4[2 * m].w, vi4[2 * m + 1].x, vi4[2 * m + 1].y, vi4[2 * m + 1].z, vi4[2 * m + 1].w};
#pragma unroll
      for (int k = 0; k < 8; k++) { vr[k] = 2.f * (vr[k] + p.x); vi[k] = -2.f * (vi[k] + p.y); p = cmul(p, lam); }
      const uint4 pr = make_uint4(pack_bf16(vr[0], vr[1]), pack_bf16(vr[2], vr[3]), pack_bf16(vr[4], vr[5]), pack_bf16(vr[6], vr[7]));
      const uint4 pi = make_uint4(pack_bf16(vi[0], vi[1]), pack_bf16(vi[2], vi[3]), pack_bf16(vi[4], vi[5]), pack_bf16(vi[6], vi[7]));
      const int m8 = qi * 4 + m;
      *reinterpret_cast<uint4*>(smem + ch * 128 + ((m8 ^ (ch & 7)) << 4)) = pr;
      *reinterpret_cast<uint4*>(smem + (DM + ch) * 128 + ((m8 ^ (ch & 7)) << 4)) = pi;
    }
  }
  fence_async_smem();
  named_bar(1, 256);
  const int wg = warp >> 2, w = warp & 3;
  float acc[112];
#pragma unroll 1
  for (int kc = 0; kc < 14; kc++) {
    const int i = kc * 2 + wg, st = i % 3;
    mbar_wait(bar + i * 8, 0);
    const uint32_t bb = sb + S2_A + st * XT_BYTES;
    wg_fence();
#pragma unroll
    for (int kk = 0; kk < 4; kk++) {
      const uint64_t da = desc_sw128(sb + (kc * 64 + kk * 16) * 128);
      wgmma_ss_n112_ta(acc, da, desc_sw128(bb + kk * 32), (kc | kk) != 0);
      wgmma_ss_n112_ta(acc + 56, da, desc_sw128(bb + 14336 + kk * 32), (kc | kk) != 0);
    }
    wg_commit();
    wg_wait<0>();
    if (lane == 0) mbar_arrive(bar + (28 + st) * 8);
  }
  const int g = lane >> 2, q = lane & 3;
  named_bar(1, 256);
  float* stg = reinterpret_cast<float*>(smem);
#pragma unroll
  for (int r = 0; r < 2; r++)
#pragma unroll
    for (int nt = 0; nt < 28; nt++)
      *reinterpret_cast<float2*>(stg + (w * 16 + g + r * 8) * 456 + wg * 224 + nt * 8 + 2 * q) = make_float2(acc[nt * 4 + r * 2], acc[nt * 4 + r * 2 + 1]);
  named_bar(1, 256);
  for (int it = tid; it < 64 * 112; it += 256) {
    const int tl = it / 112, d = (it % 112) * 4;
    const float4 y = *reinterpret_cast<const float4*>(stg + tl * 456 + d);
    const uint2 xu = *reinterpret_cast<const uint2*>(args.x + (size_t)(t0 + tl) * DM + d), du = *reinterpret_cast<const uint2*>(args.dskip + d);
    const float gv = sg[tl];
    float4 o;
    o.x = gv * (y.x + rbf(__uint_as_float(xu.x << 16) * __uint_as_float(du.x << 16)));
    o.y = gv * (y.y + rbf(__uint_as_float(xu.x & 0xFFFF0000u) * __uint_as_float(du.x & 0xFFFF0000u)));
    o.z = gv * (y.z + rbf(__uint_as_float(xu.y << 16) * __uint_as_float(du.y << 16)));
    o.w = gv * (y.w + rbf(__uint_as_float(xu.y & 0xFFFF0000u) * __uint_as_float(du.y & 0xFFFF0000u)));
    red_v4(args.out + (size_t)(t0 + tl) * DM + d, o.x, o.y, o.z, o.w);
  }
  KT_END(2);
}
struct AttnArgs {
  uint32_t* flag;
  uint32_t* ticket;
  const float* omg;
  float* out;
  uint32_t total_ctas;
};
#define AT_SPLIT_V 56
constexpr int AT_SPLIT = AT_SPLIT_V;
constexpr int AT_ITEMS = AT_SPLIT * 2 + (NSEG - AT_SPLIT) * 8;
constexpr int AT_X = 2 * 7 * 4096;
constexpr int AT_T = 7 * 5120;
constexpr int AT_OFF_K = AT_X, AT_OFF_Y = AT_X + 2 * AT_T;
constexpr int AT_OFF_P = AT_X + 4 * AT_T;
constexpr int AT_OFF_BAR = AT_OFF_P + 2 * 2 * 3072;
constexpr int AT_STG = 32 * 68 * 4;
constexpr int AT_OFF_STG = AT_OFF_BAR + 256;
constexpr int AT_SMEM = AT_OFF_STG + 2 * AT_STG;
constexpr uint32_t FLAG_TARGET = 112;

__device__ __forceinline__ void attn_decode(int item, int& s, int& p0, int& np) {
  if (item < AT_SPLIT * 2) { s = item >> 1; p0 = (item & 1) * 4; np = 4; }
  else { const int i = item - AT_SPLIT * 2; s = AT_SPLIT + (i >> 3); p0 = i & 7; np = 1; }
}

#define ATS(i) do {} while (0)
__device__ __forceinline__ void attn_consumer(uint8_t* smem, uint32_t sb, const AttnArgs& args, int wg, int w, int lane) {
  const uint32_t bar = sb + AT_OFF_BAR;
  volatile int* s_item = reinterpret_cast<volatile int*>(smem + AT_OFF_BAR + 128);
  float* stg = reinterpret_cast<float*>(smem + AT_OFF_STG + wg * AT_STG);
  const int g = lane >> 2, q = lane & 3;
  const int C0 = wg * 4;
  int m = 0;
  long long tprev = clock64(); (void)tprev;
  for (int n = 0;; n++) {
    mbar_wait(bar + (0 + (n & 1)) * 8, (n >> 1) & 1);
    ATS(0);
    const int item = s_item[n & 1];
    if (item >= AT_ITEMS) break;
    int s, p0, np;
    attn_decode(item, s, p0, np);
    const uint64_t dx = desc_sw128(sb + (n & 1) * (7 * 4096));
    float acc[4][16];
    float om4[4];
#pragma unroll
    for (int i = 0; i < 4; i++) om4[i] = args.omg[s * SEG + i * 8 + ((w * 32 + lane) >> 4)];
#pragma unroll 1
    for (int pp = 0; pp < np; pp++, m++) {
      const uint64_t dk = desc_sw128(sb + AT_OFF_K + wg * AT_T);
      mbar_wait(bar + 4 * 8, m & 1);
      ATS(1);
      float sc[20];
      wg_fence();
#pragma unroll
      for (int kc = 0; kc < 7; kc++)
#pragma unroll
        for (int kk = 0; kk < 4; kk++) wgmma_ss_n40(sc, dx + (uint64_t)(kc * 256 + kk * 2), dk + (uint64_t)(kc * 320 + kk * 2), (kc | kk) != 0);
      wg_commit();
      wg_wait<0>();
      __syncwarp();
      if (lane == 0) { mbar_arrive(bar + 5 * 8); if (pp == np - 1) mbar_arrive(bar + (2 + (n & 1)) * 8); }
      ATS(2);
      const uint32_t pbuf = sb + AT_OFF_P + (m & 1) * (2 * 3072);
      if (w < 2) {
#pragma unroll
        for (int r = 0; r < 2; r++) {
          const int t = w * 16 + g + r * 8;
          float v[10];
          float mx = -3.0e38f;
#pragma unroll
          for (int nt = 0; nt < 5; nt++)
#pragma unroll
            for (int e = 0; e < 2; e++) {
              const int key = nt * 8 + 2 * q + e;
              const float x = (key - NMEM <= t) ? sc[nt * 4 + r * 2 + e] : -1.0e9f;
              v[nt * 2 + e] = x; mx = fmaxf(mx, x);
            }
          mx = fmaxf(mx, __shfl_xor_sync(~0u, mx, 1));
          mx = fmaxf(mx, __shfl_xor_sync(~0u, mx, 2));
          float l = 0.f;
#pragma unroll
          for (int k = 0; k < 10; k++) { v[k] = ex2((v[k] - mx) * L2E); l += v[k]; }
          l += __shfl_xor_sync(~0u, l, 1);
          l += __shfl_xor_sync(~0u, l, 2);
          const float rl = __fdividef(1.f, l);
          const uint32_t dst = pbuf + wg * 3072 + (2 * w + r) * 768 + g * 16 + q * 4;
#pragma unroll
          for (int nt = 0; nt < 5; nt++) asm volatile("st.shared.u32 [%0], %1;" ::"r"(dst + nt * 128), "r"(pack_bf16(v[2 * nt] * rl, v[2 * nt + 1] * rl)) : "memory");
        }
        fence_async_smem();
      }
      ATS(3);
      named_bar(1, 256);
      ATS(4);
      const uint64_t dp = ((uint64_t)((pbuf & 0x3FFFF) >> 4)) | ((uint64_t)(128 >> 4) << 16) | ((uint64_t)(768 >> 4) << 32);
      const uint64_t dy = desc_sw128(sb + AT_OFF_Y);
      mbar_wait(bar + 6 * 8, m & 1);
      ATS(5);
      wg_fence();
#pragma unroll
      for (int c = 0; c < 4; c++) {
        const int cc = min(C0 + c, 6);
#pragma unroll
        for (int hk = 0; hk < 6; hk++) {
          const int hd = hk / 3, kk = hk % 3;
          wgmma_ss_n32_ta(acc[c], dy + (uint64_t)(hd * (AT_T >> 4) + cc * 320 + kk * 128), dp + (uint64_t)(hd * 192 + kk * 16), (pp | hk) != 0);
        }
      }
      wg_commit();
      wg_wait<0>();
      __syncwarp();
      if (lane == 0) mbar_arrive(bar + 7 * 8);
      ATS(6);
    }
    {
      const int tid7 = w * 32 + lane;
#pragma unroll
      for (int c = 0; c < 4; c++) {
        if (C0 + c < 7) {
#pragma unroll
          for (int nt = 0; nt < 4; nt++) {
            stg[(8 * nt + 2 * q) * 68 + 16 * w + g] = acc[c][4 * nt];
            stg[(8 * nt + 2 * q + 1) * 68 + 16 * w + g] = acc[c][4 * nt + 1];
            stg[(8 * nt + 2 * q) * 68 + 16 * w + g + 8] = acc[c][4 * nt + 2];
            stg[(8 * nt + 2 * q + 1) * 68 + 16 * w + g + 8] = acc[c][4 * nt + 3];
          }
          named_bar(2 + wg, 128);
#pragma unroll
          for (int i = 0; i < 4; i++) {
            const int row = i * 8 + (tid7 >> 4), col = (tid7 & 15) * 4;
            const float4 v = *reinterpret_cast<const float4*>(stg + row * 68 + col);
            const float om = om4[i];
            red_v4(args.out + (size_t)(s * SEG + row) * DM + (C0 + c) * 64 + col, om * v.x, om * v.y, om * v.z, om * v.w);
          }
          named_bar(2 + wg, 128);
        }
      }
    }
    ATS(7);
  }
}

__global__ void __launch_bounds__(384, 1)
attn_kernel(const __grid_constant__ CUtensorMap tm_x, const __grid_constant__ CUtensorMap tm_k, const __grid_constant__ CUtensorMap tm_y, AttnArgs args) {
  extern __shared__ __align__(1024) uint8_t smem[];
  const uint32_t sb = smem_u32(smem), bar = sb + AT_OFF_BAR;
  volatile int* s_item = reinterpret_cast<volatile int*>(smem + AT_OFF_BAR + 128);
  const int tid = threadIdx.x, warp = tid >> 5, lane = tid & 31;
  KT_START(3);
  if (tid == 0) {
    mbar_init(bar + 0 * 8, 1); mbar_init(bar + 1 * 8, 1); mbar_init(bar + 2 * 8, 8); mbar_init(bar + 3 * 8, 8);
    mbar_init(bar + 4 * 8, 1); mbar_init(bar + 5 * 8, 8); mbar_init(bar + 6 * 8, 1); mbar_init(bar + 7 * 8, 8);
    asm volatile("fence.mbarrier_init.release.cluster;" ::: "memory");
  }
  for (int i = tid; i < AT_OFF_BAR / 16; i += 384) *reinterpret_cast<uint4*>(smem + i * 16) = make_uint4(0, 0, 0, 0);
  fence_async_smem();
  __syncthreads();
  const int wg = __shfl_sync(0xffffffffu, warp >> 2, 0);
  if (wg == 2) {
    asm volatile("setmaxnreg.dec.sync.aligned.u32 40;");
    if (tid == 256) {
      int m = 0;
      for (int n = 0;; n++) {
        const int sl = n & 1;
        if (n >= 2) mbar_wait(bar + (2 + sl) * 8, ((n >> 1) - 1) & 1);
        const int item = (int)atomicAdd(args.ticket, 1u);
        s_item[sl] = item;
        if (item >= AT_ITEMS) {
          mbar_arrive(bar + sl * 8);
          if (atomicAdd(args.ticket + 1, 1u) == args.total_ctas - 1) {
            for (int i = 0; i < NSEG; i++) args.flag[i] = 0u;
            args.ticket[0] = 0u; args.ticket[1] = 0u;
          }
          break;
        }
        int s, p0, np;
        attn_decode(item, s, p0, np);
        mbar_expect_tx(bar + sl * 8, 7 * 4096);
        tma_load_3d(sb + sl * (7 * 4096), &tm_x, 0, s * SEG, 0, bar + sl * 8);
        { int it = 0; while (ld_acquire(args.flag + s) < FLAG_TARGET && ++it < SPIN_LIMIT) __nanosleep(100); }
        fence_async_all();
        for (int pp = 0; pp < np; pp++, m++) {
          const int row = (((p0 + pp) * 2) * NSEG + s) * LKEY;
          if (m >= 1) mbar_wait(bar + 5 * 8, (m - 1) & 1);
          mbar_expect_tx(bar + 4 * 8, 2 * AT_T);
          tma_load_3d(sb + AT_OFF_K, &tm_k, 0, row, 0, bar + 4 * 8);
          tma_load_3d(sb + AT_OFF_K + AT_T, &tm_k, 0, row + NSEG * LKEY, 0, bar + 4 * 8);
          if (m >= 1) mbar_wait(bar + 7 * 8, (m - 1) & 1);
          mbar_expect_tx(bar + 6 * 8, 2 * AT_T);
          tma_load_3d(sb + AT_OFF_Y, &tm_y, 0, row, 0, bar + 6 * 8);
          tma_load_3d(sb + AT_OFF_Y + AT_T, &tm_y, 0, row + NSEG * LKEY, 0, bar + 6 * 8);
        }
      }
    }
  } else {
    asm volatile("setmaxnreg.inc.sync.aligned.u32 232;");
    attn_consumer(smem, sb, args, wg, warp & 3, lane);
    KT_END(3);
  }
}
__device__ bf16 g_Kall[(size_t)NH * NSEG * LKEY * DM];
__device__ bf16 g_Yall[(size_t)NH * NSEG * LKEY * DM];
__device__ uint32_t g_M[65 * 1792 * 16];
__device__ float4 g_S[(size_t)NSEG * NH * 5 * 32 + (size_t)NSEG * NJ * 16 * 16 * 8];
__device__ uint32_t g_flag[NSEG + 64];
__device__ float g_hloc[2 * DM * SEQ];
__device__ float2 g_hend[16 * DM];
__device__ float g_omg[2 * SEQ];
__device__ float4 g_tab[2 * DM];
__device__ uint32_t g_dbg[112 * 1024 + 112 * 4 + 112 * 8];

typedef CUresult (*EncodeFn)(CUtensorMap*, CUtensorMapDataType, cuuint32_t, void*, const cuuint64_t*, const cuuint64_t*, const cuuint32_t*,
                             const cuuint32_t*, CUtensorMapInterleave, CUtensorMapSwizzle, CUtensorMapL2promotion, CUtensorMapFloatOOBfill);

static bool make_map_2d(EncodeFn enc, CUtensorMap* m, const void* ptr, uint64_t cols, uint64_t rows, uint32_t box_cols, uint32_t box_rows) {
  cuuint64_t dims[2] = {cols, rows};
  cuuint64_t strides[1] = {cols * 2};
  cuuint32_t box[2] = {box_cols, box_rows};
  cuuint32_t es[2] = {1, 1};
  return enc(m, CU_TENSOR_MAP_DATA_TYPE_BFLOAT16, 2, const_cast<void*>(ptr), dims, strides, box, es, CU_TENSOR_MAP_INTERLEAVE_NONE,
             CU_TENSOR_MAP_SWIZZLE_128B, CU_TENSOR_MAP_L2_PROMOTION_L2_256B, CU_TENSOR_MAP_FLOAT_OOB_FILL_NONE) == CUDA_SUCCESS;
}
static bool make_map_rows(EncodeFn enc, CUtensorMap* m, const void* ptr, uint64_t rows, uint32_t box_rows) {
  cuuint64_t dims[3] = {64, rows, 7};
  cuuint64_t strides[2] = {(cuuint64_t)DM * 2, 128};
  cuuint32_t box[3] = {64, box_rows, 7};
  cuuint32_t es[3] = {1, 1, 1};
  return enc(m, CU_TENSOR_MAP_DATA_TYPE_BFLOAT16, 3, const_cast<void*>(ptr), dims, strides, box, es, CU_TENSOR_MAP_INTERLEAVE_NONE,
             CU_TENSOR_MAP_SWIZZLE_128B, CU_TENSOR_MAP_L2_PROMOTION_L2_256B, CU_TENSOR_MAP_FLOAT_OOB_FILL_NONE) == CUDA_SUCCESS;
}
static bool make_map_xperm(EncodeFn enc, CUtensorMap* m, const void* ptr) {
  cuuint64_t dims[4] = {(cuuint64_t)DM, 2, 64, 16};
  cuuint64_t strides[3] = {(cuuint64_t)DM * 2, (cuuint64_t)DM * 2 * 32, (cuuint64_t)DM * 2 * 2};
  cuuint32_t box[4] = {64, 2, 4, 16};
  cuuint32_t es[4] = {1, 1, 1, 1};
  return enc(m, CU_TENSOR_MAP_DATA_TYPE_BFLOAT16, 4, const_cast<void*>(ptr), dims, strides, box, es, CU_TENSOR_MAP_INTERLEAVE_NONE,
             CU_TENSOR_MAP_SWIZZLE_128B, CU_TENSOR_MAP_L2_PROMOTION_L2_256B, CU_TENSOR_MAP_FLOAT_OOB_FILL_NONE) == CUDA_SUCCESS;
}

#define N_ATTN 8
struct HostState {
  bool init, ok, use_cluster;
  CUtensorMap tx, tq, tk, tv, to, tka, tya, tbre, tbim, txp, tcre, tcim, tx3, tk3, ty3;
  void *pK, *pY, *pM, *pS, *pF, *pD, *pH, *pE, *pO, *pT;
  cudaStream_t side, side2;
  cudaEvent_t ev_start, ev_join, ev_gate, ev_join2;
  int n_free, n_attn;
  const void* key[17];
  void* key_out;
};
static HostState g_hs;

}

extern "C" void kernel_launch(void* const* d_in, const int* in_sizes, int n_in, void* d_out, int out_size) {
  HostState& S = g_hs;
  (void)in_sizes; (void)n_in; (void)out_size;
  cudaStream_t st = cudaStreamPerThread;
  bool same = S.init;
  for (int i = 0; i < 17 && same; i++) same = S.key[i] == d_in[i];
  if (!same) {
    EncodeFn enc = nullptr;
    cudaDriverEntryPointQueryResult qr;
    cudaGetDriverEntryPoint("cuTensorMapEncodeTiled", (void**)&enc, cudaEnableDefault, &qr);
    cudaGetSymbolAddress(&S.pK, g_Kall); cudaGetSymbolAddress(&S.pY, g_Yall); cudaGetSymbolAddress(&S.pM, g_M); cudaGetSymbolAddress(&S.pS, g_S);
    cudaGetSymbolAddress(&S.pF, g_flag); cudaGetSymbolAddress(&S.pD, g_dbg); cudaGetSymbolAddress(&S.pH, g_hloc); cudaGetSymbolAddress(&S.pE, g_hend);
    cudaGetSymbolAddress(&S.pO, g_omg); cudaGetSymbolAddress(&S.pT, g_tab);
    S.ok = enc && make_map_2d(enc, &S.tx, d_in[0], DM, SEQ, 64, 32) && make_map_2d(enc, &S.tq, d_in[11], 4096, DM, 64, 64) &&
           make_map_2d(enc, &S.tk, d_in[12], 4096, DM, 64, 224) && make_map_2d(enc, &S.tv, d_in[13], 4096, DM, 64, 224) &&
           make_map_2d(enc, &S.to, d_in[14], DM, 4096, 64, 256) && make_map_2d(enc, &S.tka, S.pK, DM, NH * NSEG * LKEY, 64, LKEY) &&
           make_map_2d(enc, &S.tya, S.pY, DM, NH * NSEG * LKEY, 64, LKEY) && make_map_2d(enc, &S.tbre, d_in[3], DM, DM, 64, 64) &&
           make_map_2d(enc, &S.tbim, d_in[4], DM, DM, 64, 64) && make_map_xperm(enc, &S.txp, d_in[0]) &&
           make_map_2d(enc, &S.tcre, d_in[5], DM, DM, 64, 224) && make_map_2d(enc, &S.tcim, d_in[6], DM, DM, 64, 224) &&
           make_map_rows(enc, &S.tx3, d_in[0], SEQ, SEG) && make_map_rows(enc, &S.tk3, S.pK, NH * NSEG * LKEY, LKEY) && make_map_rows(enc, &S.ty3, S.pY, NH * NSEG * LKEY, LKEY);
    if (!S.init) {
      cudaFuncSetAttribute(chain_kernel<true>, cudaFuncAttributeMaxDynamicSharedMemorySize, SMEM_CHAIN);
      cudaFuncSetAttribute(chain_kernel<true>, cudaFuncAttributeNonPortableClusterSizeAllowed, 1);
      cudaFuncSetAttribute(chain_kernel<false>, cudaFuncAttributeMaxDynamicSharedMemorySize, SMEM_CHAIN);
      cudaFuncSetAttribute(ssm1_kernel, cudaFuncAttributeMaxDynamicSharedMemorySize, S1_SMEM);
      cudaFuncSetAttribute(ssm2_kernel, cudaFuncAttributeMaxDynamicSharedMemorySize, S2_SMEM);
      cudaFuncSetAttribute(attn_kernel, cudaFuncAttributeMaxDynamicSharedMemorySize, AT_SMEM);
      cudaLaunchConfig_t cfg = {};
      cfg.gridDim = dim3(112); cfg.blockDim = dim3(CHAIN_THREADS); cfg.dynamicSmemBytes = SMEM_CHAIN;
      cudaLaunchAttribute at[1];
      at[0].id = cudaLaunchAttributeClusterDimension; at[0].val.clusterDim.x = 16; at[0].val.clusterDim.y = 1; at[0].val.clusterDim.z = 1;
      cfg.attrs = at; cfg.numAttrs = 1;
      int nc = 0;
      if (cudaOccupancyMaxActiveClusters(&nc, chain_kernel<true>, &cfg) != cudaSuccess) { nc = 0; (void)cudaGetLastError(); }
      S.use_cluster = nc >= 7;
      int sms = 132;
      cudaDeviceGetAttribute(&sms, cudaDevAttrMultiProcessorCount, 0);
      S.n_free = sms - 112 > 1 ? sms - 112 : 1;
      S.n_attn = S.n_free >= 16 ? N_ATTN : (S.n_free + 1) / 2;
      cudaStreamCreateWithFlags(&S.side, cudaStreamNonBlocking);
      cudaEventCreateWithFlags(&S.ev_start, cudaEventDisableTiming);
      cudaEventCreateWithFlags(&S.ev_join, cudaEventDisableTiming);
      cudaStreamCreateWithFlags(&S.side2, cudaStreamNonBlocking);
      cudaEventCreateWithFlags(&S.ev_gate, cudaEventDisableTiming);
      cudaEventCreateWithFlags(&S.ev_join2, cudaEventDisableTiming);
    }
    for (int i = 0; i < 17; i++) S.key[i] = d_in[i];
    S.init = true;
  }
  if (!S.ok) return;

  ChainArgs ca;
  ca.mem0 = (const bf16*)d_in[10]; ca.Mg = (uint32_t*)S.pM; ca.Sg = (float4*)S.pS; ca.flag = (uint32_t*)S.pF; ca.dbg = (uint32_t*)S.pD;
  {
    cudaLaunchConfig_t cfg = {};
    cfg.gridDim = dim3(112); cfg.blockDim = dim3(CHAIN_THREADS); cfg.dynamicSmemBytes = SMEM_CHAIN; cfg.stream = st;
    cudaLaunchAttribute at[2];
    at[0].id = cudaLaunchAttributeLaunchCompletionEvent; at[0].val.launchCompletionEvent.event = S.ev_start; at[0].val.launchCompletionEvent.flags = 0;
    at[1].id = cudaLaunchAttributeClusterDimension; at[1].val.clusterDim.x = 16; at[1].val.clusterDim.y = 1; at[1].val.clusterDim.z = 1;
    cfg.attrs = at; cfg.numAttrs = S.use_cluster ? 2 : 1;
    if (S.use_cluster) cudaLaunchKernelEx(&cfg, chain_kernel<true>, S.tx, S.tq, S.tk, S.tv, S.to, S.tka, S.tya, S.tx3, ca);
    else cudaLaunchKernelEx(&cfg, chain_kernel<false>, S.tx, S.tq, S.tk, S.tv, S.to, S.tka, S.tya, S.tx3, ca);
  }
  SsmArgs sa;
  sa.lam_re = (const bf16*)d_in[1]; sa.lam_im = (const bf16*)d_in[2]; sa.log_dt = (const bf16*)d_in[7]; sa.dskip = (const bf16*)d_in[8];
  sa.x = (const bf16*)d_in[0]; sa.gate_w = (const bf16*)d_in[16];
  sa.hloc = (float*)S.pH; sa.hend = (float2*)S.pE; sa.omg = (float*)S.pO; sa.gate = (float*)S.pO + SEQ; sa.tab = (float4*)S.pT; sa.out = (float*)d_out;
  AttnArgs aa;
  aa.flag = (uint32_t*)S.pF; aa.ticket = (uint32_t*)S.pF + NSEG; aa.omg = (const float*)S.pO; aa.out = (float*)d_out;
  const int n_attn2 = S.n_free - S.n_attn > 0 ? S.n_free - S.n_attn : 0;
  aa.total_ctas = (uint32_t)(S.n_attn + n_attn2);
  cudaStreamWaitEvent(S.side, S.ev_start, 0);
  cudaMemsetAsync(d_out, 0, sizeof(float) * SEQ * DM, S.side);
  gate_kernel<<<64, 128, 0, S.side>>>(sa);
  cudaEventRecord(S.ev_gate, S.side);
  attn_kernel<<<S.n_attn, 384, AT_SMEM, S.side>>>(S.tx3, S.tk3, S.ty3, aa);
  cudaStreamWaitEvent(S.side2, S.ev_gate, 0);
  ssm1_kernel<<<dim3(7, 16), 160, S1_SMEM, S.side2>>>(S.tbre, S.tbim, S.txp, sa);
  ssm2_kernel<<<32, 288, S2_SMEM, S.side2>>>(S.tcre, S.tcim, sa);
  if (n_attn2 > 0) attn_kernel<<<n_attn2, 384, AT_SMEM, S.side2>>>(S.tx3, S.tk3, S.ty3, aa);
  cudaEventRecord(S.ev_join, S.side);
  cudaEventRecord(S.ev_join2, S.side2);
  cudaStreamWaitEvent(st, S.ev_join, 0);
  cudaStreamWaitEvent(st, S.ev_join2, 0);
}
```
